```python
import torch

def _softmax(x, axis=-1):
    return torch.softmax(x, dim=axis)
def _gelu(x):
    return torch.nn.functional.gelu(x, approximate="tanh")
def _silu(x):
    return torch.nn.functional.silu(x)
def _sigmoid(x):
    return torch.sigmoid(x)
def _layernorm(x, axis=-1, eps=1e-5):
    m = x.mean(dim=axis, keepdim=True)
    v = x.var(dim=axis, keepdim=True, unbiased=False)
    return (x - m) / torch.sqrt(v + eps)
def _scatter_add(tgt, idx, src, axis=0):
    return tgt.clone().index_add_(axis, idx, src)
def _segment_sum(src, seg, n):
    out = torch.zeros((n,) + src.shape[1:], dtype=src.dtype)
    return out.index_add_(0, seg, src)
def _pad(x, pw):
    flat = tuple(v for pair in reversed(pw) for v in pair)
    return torch.nn.functional.pad(x, flat)

kernel_name = 'concat_heads__gqa_block_cached__mha_block_cached__near_ridge'

def setup_inputs():

    _w = (lambda a: (lambda t: t.to(torch.bfloat16) if t.is_floating_point() else t)(torch.as_tensor(a)))
    def _A_setup():
        B, Sq, D = 8, 144, 512
        Hq, Hkv, Sk, Dh = 32, 32, 512, 128
        assert Hq % Hkv == 0, (Hq, Hkv)
        return {
            "x": _w((lambda *s: torch.randn(*s, dtype=torch.bfloat16) * 0.8)(B, Sq, D)),
            "k_cache": _w((lambda *s: torch.randn(*s, dtype=torch.bfloat16) * 0.8)(B, Hkv, Sk, Dh)),
            "v_cache": _w((lambda *s: torch.randn(*s, dtype=torch.bfloat16) * 0.05)(B, Hkv, Sk, Dh)),
            "wq": _w((lambda *s: torch.randn(*s, dtype=torch.bfloat16) * 0.8)(D, Hq * Dh) * (D ** -0.5)),
            "wo": _w((lambda *s: torch.randn(*s, dtype=torch.bfloat16) * 0.05)(Hq * Dh, D) * ((Hq * Dh) ** -0.5)),
        }
    _A_in = _A_setup()

    def _B_setup():
        B, Sq, D = 8, 144, 512
        H, Sk, Dh = 32, 512, 128
        return {
            "x": _w((lambda *s: torch.randn(*s, dtype=torch.bfloat16) * 0.8)(B, Sq, D)),
            "k_cache": _w((lambda *s: torch.randn(*s, dtype=torch.bfloat16) * 0.8)(B, H, Sk, Dh)),
            "v_cache": _w((lambda *s: torch.randn(*s, dtype=torch.bfloat16) * 0.05)(B, H, Sk, Dh)),
            "wq": _w((lambda *s: torch.randn(*s, dtype=torch.bfloat16) * 0.8)(D, H * Dh) * (D ** -0.5)),
            "wo": _w((lambda *s: torch.randn(*s, dtype=torch.bfloat16) * 0.05)(H * Dh, D) * ((H * Dh) ** -0.5)),
        }
    _B_in = _B_setup()

    return {
        "A_x": _A_in["x"],
        "A_k_cache": _A_in["k_cache"],
        "A_v_cache": _A_in["v_cache"],
        "A_wq": _A_in["wq"],
        "A_wo": _A_in["wo"],
        "B_x": _B_in["x"],
        "B_k_cache": _B_in["k_cache"],
        "B_v_cache": _B_in["v_cache"],
        "B_wq": _B_in["wq"],
        "B_wo": _B_in["wo"],
    }

def reference(A_x, A_k_cache, A_v_cache, A_wq, A_wo, B_x, B_k_cache, B_v_cache, B_wq, B_wo):
    def _A_ref(x, k_cache, v_cache, wq, wo):
        B, Sq, D = x.shape
        Hq, Dh = 32, 128
        Hkv = k_cache.shape[1]
        rep = Hq // Hkv
        q = (lambda x, *d: x.permute(*d))((x @ wq).reshape(B, Sq, Hq, Dh), 0, 2, 1, 3)
        k = (lambda x, n, axis: torch.repeat_interleave(x, n, dim=axis))(k_cache, rep, axis=1)
        v = (lambda x, n, axis: torch.repeat_interleave(x, n, dim=axis))(v_cache, rep, axis=1)
        scores = torch.einsum("bhqd,bhkd->bhqk", q, k) * (Dh ** -0.5)
        p = _softmax(scores, axis=-1)
        o = torch.einsum("bhqk,bhkd->bhqd", p, v)
        return (lambda x, *d: x.permute(*d))(o, 0, 2, 1, 3).reshape(B, Sq, Hq * Dh) @ wo

    def _B_ref(x, k_cache, v_cache, wq, wo):
        B, Sq, D = x.shape
        H, Dh = 32, 128
        q = (lambda x, *d: x.permute(*d))((x @ wq).reshape(B, Sq, H, Dh), 0, 2, 1, 3)
        scores = torch.einsum("bhqd,bhkd->bhqk", q, k_cache) * (Dh ** -0.5)
        p = _softmax(scores, axis=-1)
        o = torch.einsum("bhqk,bhkd->bhqd", p, v_cache)
        return (lambda x, *d: x.permute(*d))(o, 0, 2, 1, 3).reshape(B, Sq, H * Dh) @ wo

    a = _A_ref(A_x, A_k_cache, A_v_cache, A_wq, A_wo)
    b = _B_ref(B_x, B_k_cache, B_v_cache, B_wq, B_wo)
    return torch.concatenate([a, b], axis=-1)
```

```cpp
#include <cuda_runtime.h>
#include <cuda_bf16.h>
#include <cuda.h>
#include <stdint.h>
#define DBG_SYNC(tag)

namespace {

constexpr int NBATCH = 8, SQ = 144, DM = 512, NH = 32, DH = 128, SK = 512;
constexpr int NGRP = 16;
constexpr int BT = SQ * 128;
constexpr int AT = 64 * 128;
constexpr int QIMG = 2 * BT;
constexpr int NTHREADS = 512;
constexpr int SMEM_BYTES = 232448;
constexpr uint32_t WAIT_LIMIT = 1u << 20;
#define PUB_FIRST
#define PLAIN_EX2
#define L2PROMO CU_TENSOR_MAP_L2_PROMOTION_NONE
#define SIDE_THR 430
#define STAG_EXPR ((long long)(idx >= NEARLY) * STAGGER)
#define STAGGER 12000
#define NEARLY 26
#define NWK 5
#define CLUSTER 2
#define W_PF 0
#define TURN_AT 16
#define PF_DIST 0

constexpr int A_Q = 0;
constexpr int A_O = A_Q + QIMG;
constexpr int A_P = A_O + QIMG;
constexpr int A_K = A_P + 3 * BT;
constexpr int A_V = A_K + 3 * 2 * AT;
constexpr int A_L = A_V + 3 * 2 * AT;
constexpr int A_FB = A_L + SQ * 4;
constexpr int A_BAR = A_L + 8 * SQ * 4;
static_assert(A_BAR % 8 == 0 && A_BAR + 392 <= SMEM_BYTES - 16 && A_FB + 648 * 4 <= A_BAR, "att smem");
constexpr int O_NS = 4;
constexpr int O_STG = 4 * AT + BT;
constexpr int O_BAR = O_NS * O_STG;
static_assert(O_STG % 1024 == 0 && O_BAR + 256 <= SMEM_BYTES, "op smem");

struct alignas(64) Params {
  CUtensorMap tmK[2], tmV[2], tmWq[2], tmWo[2], tmX[2], tmOut;
  const __nv_bfloat16* K[2];
  const __nv_bfloat16* V[2];
  const __nv_bfloat16* X[2];
  const __nv_bfloat16* Wq[2];
  const __nv_bfloat16* Wo[2];
  int natt;
  int sidemap;
  int mode;
};

__device__ uint8_t g_O[NGRP * NH * QIMG];
__device__ uint32_t g_oflag[2][NGRP * NH];
__device__ uint32_t g_probe[64];
__device__ uint32_t g_ticket[2][32];
__device__ uint32_t g_done;

#define TSTAMP(i)
#define CSTAMP(i)
#define DSTAMP(i)
#define PH_DECL
#define PH(i)
#define PH_OUT(base)
#define EP(i)
__device__ __forceinline__ uint32_t smem_u32(const void* p) { return (uint32_t)__cvta_generic_to_shared(p); }
__device__ __forceinline__ void mbar_init(uint32_t bar, uint32_t cnt) {
  asm volatile("mbarrier.init.shared::cta.b64 [%0], %1;" ::"r"(bar), "r"(cnt) : "memory");
}
__device__ __forceinline__ void mbar_expect_tx(uint32_t bar, uint32_t bytes) {
  asm volatile("mbarrier.arrive.expect_tx.shared::cta.b64 _, [%0], %1;" ::"r"(bar), "r"(bytes) : "memory");
}
__device__ __forceinline__ void mbar_arrive(uint32_t bar) {
  asm volatile("mbarrier.arrive.shared::cta.b64 _, [%0];" ::"r"(bar) : "memory");
}
__device__ __forceinline__ void mbar_arrive2(uint32_t bar) {
  asm volatile("mbarrier.arrive.shared::cta.b64 _, [%0], 2;" ::"r"(bar) : "memory");
}
__device__ __forceinline__ uint32_t peer_addr(uint32_t addr, uint32_t peer) {
  uint32_t r;
  asm volatile("mapa.shared::cluster.u32 %0, %1, %2;" : "=r"(r) : "r"(addr), "r"(peer));
  return r;
}
__device__ __forceinline__ void mbar_arrive_remote(uint32_t rbar) {
  asm volatile("mbarrier.arrive.shared::cluster.b64 _, [%0];" ::"r"(rbar) : "memory");
}
__device__ __forceinline__ void mbar_arrive2_remote(uint32_t rbar) {
  asm volatile("mbarrier.arrive.shared::cluster.b64 _, [%0], 2;" ::"r"(rbar) : "memory");
}
__device__ __forceinline__ bool mbar_try(uint32_t bar, uint32_t parity) {
  uint32_t ok;
  asm volatile(
      "{\n.reg .pred p;\nmbarrier.try_wait.parity.shared::cta.b64 p, [%1], %2;\nselp.u32 %0, 1, 0, p;\n}\n"
      : "=r"(ok)
      : "r"(bar), "r"(parity)
      : "memory");
  return ok;
}
__device__ __forceinline__ void mbar_wait(uint32_t bar, uint32_t parity) {
  if (mbar_try(bar, parity)) return;
  uint32_t n = 0;
  while (!mbar_try(bar, parity)) {
    if (++n > WAIT_LIMIT) __trap();
  }
}
__device__ __forceinline__ void fence_async_smem() { asm volatile("fence.proxy.async.shared::cta;" ::: "memory"); }
__device__ __forceinline__ void fence_async_all() { asm volatile("fence.proxy.async;" ::: "memory"); }
__device__ __forceinline__ void named_bar(int id, int n) { asm volatile("bar.sync %0, %1;" ::"r"(id), "r"(n) : "memory"); }

__device__ __forceinline__ uint64_t policy_evict_first() {
  uint64_t p;
  asm volatile("createpolicy.fractional.L2::evict_first.b64 %0, 1.0;" : "=l"(p));
  return p;
}
__device__ __forceinline__ void tma2d(uint32_t dst, const CUtensorMap* tm, int c0, int c1, uint32_t bar) {
  asm volatile("cp.async.bulk.tensor.2d.shared::cluster.global.mbarrier::complete_tx::bytes [%0], [%1, {%3, %4}], [%2];" ::"r"(dst),
               "l"(tm), "r"(bar), "r"(c0), "r"(c1)
               : "memory");
}
__device__ __forceinline__ void tma3d(uint32_t dst, const CUtensorMap* tm, int c0, int c1, int c2, uint32_t bar) {
  asm volatile("cp.async.bulk.tensor.3d.shared::cluster.global.mbarrier::complete_tx::bytes [%0], [%1, {%3, %4, %5}], [%2];" ::"r"(dst),
               "l"(tm), "r"(bar), "r"(c0), "r"(c1), "r"(c2)
               : "memory");
}
__device__ __forceinline__ void tma3d_mc(uint32_t dst, const CUtensorMap* tm, int c0, int c1, int c2, uint32_t bar) {
  asm volatile(
      "cp.async.bulk.tensor.3d.shared::cluster.global.mbarrier::complete_tx::bytes.multicast::cluster [%0], [%1, {%3, %4, %5}], [%2], %6;" ::"r"(dst),
      "l"(tm), "r"(bar), "r"(c0), "r"(c1), "r"(c2), "h"((uint16_t)3)
      : "memory");
}
__device__ __forceinline__ void tma3d_hint(uint32_t dst, const CUtensorMap* tm, int c0, int c1, int c2, uint32_t bar, uint64_t pol) {
  asm volatile(
      "cp.async.bulk.tensor.3d.shared::cluster.global.mbarrier::complete_tx::bytes.L2::cache_hint [%0], [%1, {%3, %4, %5}], [%2], %6;" ::"r"(dst),
      "l"(tm), "r"(bar), "r"(c0), "r"(c1), "r"(c2), "l"(pol)
      : "memory");
}
__device__ __forceinline__ void tma2d_prefetch(const CUtensorMap* tm, int c0, int c1) {
  asm volatile("cp.async.bulk.prefetch.tensor.2d.L2.global [%0, {%1, %2}];" ::"l"(tm), "r"(c0), "r"(c1) : "memory");
}
__device__ __forceinline__ void tma3d_prefetch(const CUtensorMap* tm, int c0, int c1, int c2) {
  asm volatile("cp.async.bulk.prefetch.tensor.3d.L2.global [%0, {%1, %2, %3}];" ::"l"(tm), "r"(c0), "r"(c1), "r"(c2) : "memory");
}
__device__ __forceinline__ void bulk_load(uint32_t dst, const void* src, uint32_t bytes, uint32_t bar) {
  asm volatile("cp.async.bulk.shared::cluster.global.mbarrier::complete_tx::bytes [%0], [%1], %2, [%3];" ::"r"(dst), "l"(src),
               "r"(bytes), "r"(bar)
               : "memory");
}
__device__ __forceinline__ void bulk_store(void* dst, uint32_t src, uint32_t bytes) {
  asm volatile("cp.async.bulk.global.shared::cta.bulk_group [%0], [%1], %2;" ::"l"(dst), "r"(src), "r"(bytes) : "memory");
}
__device__ __forceinline__ void tma2d_store(const CUtensorMap* tm, uint32_t src, int c0, int c1) {
  asm volatile("cp.async.bulk.tensor.2d.global.shared::cta.bulk_group [%0, {%2, %3}], [%1];" ::"l"(tm), "r"(src), "r"(c0), "r"(c1)
               : "memory");
}
__device__ __forceinline__ void bulk_commit() { asm volatile("cp.async.bulk.commit_group;" ::: "memory"); }
__device__ __forceinline__ void bulk_wait_read() { asm volatile("cp.async.bulk.wait_group.read 0;" ::: "memory"); }
__device__ __forceinline__ void bulk_wait_all() { asm volatile("cp.async.bulk.wait_group 0;" ::: "memory"); }
__device__ __forceinline__ void l2_prefetch(const void* src, uint32_t bytes, uint64_t pol) {
  asm volatile("cp.async.bulk.prefetch.L2.global.L2::cache_hint [%0], %1, %2;" ::"l"(src), "r"(bytes), "l"(pol) : "memory");
}
__device__ __forceinline__ void lsu_prefetch(const void* a) { asm volatile("prefetch.global.L2 [%0];" ::"l"(a)); }
__device__ __forceinline__ void flag_add_release(uint32_t* f) {
  asm volatile("red.release.gpu.global.add.u32 [%0], 1;" ::"l"(f) : "memory");
}
__device__ __forceinline__ void flag_wait_reset(uint32_t* f, uint32_t target) {
  uint32_t v, n = 0;
  while (true) {
    asm volatile("ld.acquire.gpu.global.u32 %0, [%1];" : "=r"(v) : "l"(f) : "memory");
    if (v >= target) break;
    if (++n > (1u << 24)) __trap();
    __nanosleep(20);
  }
  asm volatile("st.relaxed.gpu.global.u32 [%0], %1;" ::"l"(f), "r"(0u) : "memory");
  fence_async_all();
}

__device__ __forceinline__ void wg_fence() { asm volatile("wgmma.fence.sync.aligned;" ::: "memory"); }
__device__ __forceinline__ void wg_commit() { asm volatile("wgmma.commit_group.sync.aligned;" ::: "memory"); }
template <int N>
__device__ __forceinline__ void wg_wait() {
  asm volatile("wgmma.wait_group.sync.aligned %0;" ::"n"(N) : "memory");
}
__device__ __forceinline__ uint64_t mkdesc(uint32_t addr) {
  return (uint64_t)((addr & 0x3FFFF) >> 4) | ((uint64_t)1 << 16) | ((uint64_t)64 << 32) | ((uint64_t)1 << 62);
}

#define ACC8(c, o) c(d[o]), c(d[o + 1]), c(d[o + 2]), c(d[o + 3]), c(d[o + 4]), c(d[o + 5]), c(d[o + 6]), c(d[o + 7])
#define ACC72(c) ACC8(c, 0), ACC8(c, 8), ACC8(c, 16), ACC8(c, 24), ACC8(c, 32), ACC8(c, 40), ACC8(c, 48), ACC8(c, 56), ACC8(c, 64)
#define WGMMA144_HEAD                                                                                                          \
  "wgmma.mma_async.sync.aligned.m64n144k16.f32.bf16.bf16 "                                                                     \
  "{%0, %1, %2, %3, %4, %5, %6, %7, %8, %9, %10, %11, %12, %13, %14, %15, %16, %17, %18, %19, %20, %21, %22, %23, "            \
  "%24, %25, %26, %27, %28, %29, %30, %31, %32, %33, %34, %35, %36, %37, %38, %39, %40, %41, %42, %43, %44, %45, %46, %47, "   \
  "%48, %49, %50, %51, %52, %53, %54, %55, %56, %57, %58, %59, %60, %61, %62, %63, %64, %65, %66, %67, %68, %69, %70, %71}, "
template <int TA, bool INIT>
__device__ __forceinline__ void wgmma144(float (&d)[72], uint64_t da, uint64_t db) {
  if constexpr (INIT) {
    asm volatile("{\n.reg .pred p;\nsetp.ne.b32 p, 0, 0;\n" WGMMA144_HEAD "%72, %73, p, 1, 1, %74, 0;\n}\n"
                 : ACC72("=f")
                 : "l"(da), "l"(db), "n"(TA));
  } else {
    asm volatile("{\n.reg .pred p;\nsetp.eq.b32 p, 0, 0;\n" WGMMA144_HEAD "%72, %73, p, 1, 1, %74, 0;\n}\n"
                 : ACC72("+f")
                 : "l"(da), "l"(db), "n"(TA));
  }
}
template <bool INIT>
__device__ __forceinline__ void mma_kblock_mn(float (&d)[72], uint64_t da, uint64_t db) {
  wgmma144<1, INIT>(d, da, db);
  wgmma144<1, false>(d, da + 128, db + 2);
  wgmma144<1, false>(d, da + 256, db + 4);
  wgmma144<1, false>(d, da + 384, db + 6);
}
template <bool INIT>
__device__ __forceinline__ void mma_kblock_mn2(float (&d0)[72], float (&d1)[72], uint64_t da, uint64_t db) {
  wgmma144<1, INIT>(d0, da, db);
  wgmma144<1, INIT>(d1, da + (AT >> 4), db);
#pragma unroll
  for (int kk = 1; kk < 4; kk++) {
    wgmma144<1, false>(d0, da + kk * 128, db + kk * 2);
    wgmma144<1, false>(d1, da + kk * 128 + (AT >> 4), db + kk * 2);
  }
}
__device__ __forceinline__ uint32_t pack_bf16(float lo, float hi) {
  uint32_t r;
  asm("cvt.rn.bf16x2.f32 %0, %1, %2;" : "=r"(r) : "f"(hi), "f"(lo));
  return r;
}
__device__ __forceinline__ void stsm_t4(uint32_t addr, uint32_t r0, uint32_t r1, uint32_t r2, uint32_t r3) {
  asm volatile("stmatrix.sync.aligned.m8n8.x4.trans.shared.b16 [%0], {%1, %2, %3, %4};" ::"r"(addr), "r"(r0), "r"(r1), "r"(r2),
               "r"(r3)
               : "memory");
}
__device__ __forceinline__ float ex2(float x) {
  float y;
  asm volatile("ex2.approx.ftz.f32 %0, %1;" : "=f"(y) : "f"(x));
  return y;
}
__device__ __forceinline__ void ex2x8_dep(float* x, uint32_t dep) {
  asm volatile(
      "{\n.reg .pred p;\nsetp.ne.u32 p, %8, 0xFFFFFFFF;\n"
      "@p ex2.approx.ftz.f32 %0, %0;\n@p ex2.approx.ftz.f32 %1, %1;\n@p ex2.approx.ftz.f32 %2, %2;\n@p ex2.approx.ftz.f32 %3, %3;\n"
      "@p ex2.approx.ftz.f32 %4, %4;\n@p ex2.approx.ftz.f32 %5, %5;\n@p ex2.approx.ftz.f32 %6, %6;\n@p ex2.approx.ftz.f32 %7, %7;\n}\n"
      : "+f"(x[0]), "+f"(x[1]), "+f"(x[2]), "+f"(x[3]), "+f"(x[4]), "+f"(x[5]), "+f"(x[6]), "+f"(x[7])
      : "r"(dep));
}
__device__ __forceinline__ uint32_t stsm_lane_off(int warp_in_wg, int lane) {
  int mi = lane >> 3, rr = lane & 7;
  return (uint32_t)(((mi >> 1) * 8 + rr) * 128 + (((2 * warp_in_wg + (mi & 1)) ^ rr) << 4));
}
__device__ __forceinline__ void store_tile_scaled(const float (&d)[72], uint32_t base, float s) {
#pragma unroll
  for (int j = 0; j < 18; j += 2) {
    stsm_t4(base + j * 1024, pack_bf16(d[4 * j] * s, d[4 * j + 1] * s), pack_bf16(d[4 * j + 2] * s, d[4 * j + 3] * s),
            pack_bf16(d[4 * j + 4] * s, d[4 * j + 5] * s), pack_bf16(d[4 * j + 6] * s, d[4 * j + 7] * s));
  }
}

struct AttBars {
  uint32_t kw_full, k_full, k_empty, vw_full, v_full, v_empty, x_full, p_full, b_empty, xq_full, xq_empty, s_done, qp_done, q_ready,
      l_ready, li_ready, o_full, o_empty, turn;
  __device__ __forceinline__ AttBars(uint32_t b)
      : kw_full(b), k_full(b + 24), k_empty(b + 72), vw_full(b + 96), v_full(b + 120), v_empty(b + 144), x_full(b + 168),
        p_full(b + 192), b_empty(b + 216), xq_full(b + 240), xq_empty(b + 256), s_done(b + 272), qp_done(b + 280),
        q_ready(b + 288), l_ready(b + 296), li_ready(b + 304), o_full(b + 312), o_empty(b + 320), turn(b + 328) {}
};
constexpr int ATT_BAR_BYTES = 328 + 64;
struct HeadList { int blk, i0, i1, stride; };
struct HeadId { int g, h; };
__device__ __forceinline__ HeadId att_head(const HeadList& hl, int r) {
  const int hi = r == 0 ? hl.i0 : hl.i1 + (r - 1) * hl.stride;
  return {hl.blk * 8 + (hi & 7), hi >> 3};
}
#define KVROW(id) ((((id).g & 7) * NH + (id).h) * SK)

__device__ __forceinline__ void att_producer(const Params& p, uint32_t sb, const HeadList& hl, int rank, int nheads, int warp,
                                             int lane) {
  const AttBars B(sb + A_BAR);
  if (lane != 0 && warp != 3) return;
  if (warp == 0 || warp == 1) {
    const bool isk = warp == 0;
    const int nw = isk ? NWK : 8 - NWK, w0 = isk ? 0 : NWK;
    const uint32_t base = sb + (isk ? A_K : A_V), empty = isk ? B.k_empty : B.v_empty, wfull = isk ? B.kw_full : B.vw_full;
    const uint64_t pol = policy_evict_first();
    int slot = 0, n6 = 0;
    uint32_t ph = 1;
    for (int r = 0; r < nheads; r++) {
      const HeadId id = att_head(hl, r);
      const int blk = id.g >> 3;
      for (int j = 0; j < nw + 8; j++) {
        const uint32_t dst = base + slot * 2 * AT;
        mbar_wait(empty + 8 * slot, ph);
        if (j < nw) {
          if (r == 2) DSTAMP(20 + w0 + j);
          mbar_expect_tx(wfull + 8 * slot, 2 * AT);
          tma3d_mc(dst + rank * AT, &p.tmWq[blk], 0, (w0 + j) * 64, id.h * 2 + rank, wfull + 8 * slot);
        } else {
          const uint32_t full = isk ? B.k_full + 8 * n6 : B.v_full + 8 * slot;
          mbar_expect_tx(full, 2 * AT);
          tma3d_hint(dst, isk ? &p.tmK[blk] : &p.tmV[blk], 0, KVROW(id) + (j - nw) * 64, 0, full, pol);
          if (++n6 == 6) n6 = 0;
        }
        if (++slot == 3) { slot = 0; ph ^= 1; }
      }
    }
  } else if (warp == 2) {
    int slot = 0;
    uint32_t ph = 1;
    for (int r = 0; r < nheads; r++) {
      const HeadId id = att_head(hl, r);
      const CUtensorMap* tm = &p.tmX[id.g >> 3];
      const int row = (id.g & 7) * SQ;
      auto load_q = [&](int j) {
        if (r == 2) DSTAMP(30 + j);
        mbar_expect_tx(B.xq_full + 8 * (j == 0 || j == 5 ? 0 : 1), BT);
        tma2d(sb + A_Q + (j == 0 || j == 5 ? 0 : BT), tm, j * 64, row, B.xq_full + 8 * (j == 0 || j == 5 ? 0 : 1));
      };
      auto load_b = [&](int j) {
        mbar_wait(B.b_empty + 8 * slot, ph);
        if (r == 2) DSTAMP(30 + j);
        mbar_expect_tx(B.x_full + 8 * slot, BT);
        tma2d(sb + A_P + slot * BT, tm, j * 64, row, B.x_full + 8 * slot);
        if (++slot == 3) { slot = 0; ph ^= 1; }
      };
      if (r > 0) mbar_wait(B.s_done, (r - 1) & 1);
      load_q(0);
      load_q(1);
      load_b(2);
      load_b(3);
      load_b(4);
      mbar_wait(B.xq_empty, r & 1);
      load_q(5);
      mbar_wait(B.xq_empty + 8, r & 1);
      load_q(6);
      load_b(7);
      for (int t = 0; t < 8; t++) {
        mbar_wait(B.b_empty + 8 * slot, ph);
        if (++slot == 3) { slot = 0; ph ^= 1; }
      }
    }
  } else {
    auto prefetch_w = [&](int r) {
      const HeadId id = att_head(hl, r);
      const uint8_t* src = (const uint8_t*)((id.g >> 3) ? p.Wq[1] : p.Wq[0]) + (id.h * DH + rank * 64) * 2 + (size_t)lane * (NH * DH * 2);
#pragma unroll 4
      for (int k = 0; k < 16; k++) lsu_prefetch(src + (size_t)k * 32 * (NH * DH * 2));
    };
    if (W_PF == 1 && nheads > 1) prefetch_w(1);
    for (int r = 0; r < nheads; r++) {
      if (lane == 0) {
        const HeadId id = att_head(hl, r);
        const int hh = id.g * NH + id.h;
        mbar_wait(B.o_full, r & 1);
        bulk_store(g_O + (size_t)hh * QIMG, sb + A_O, QIMG);
        bulk_commit();
        bulk_wait_read();
        mbar_arrive(B.o_empty);
        bulk_wait_all();
        fence_async_all();
        asm volatile("fence.acq_rel.gpu;" ::: "memory");
        asm volatile("red.relaxed.gpu.global.add.u32 [%0], 1;" ::"l"(&g_oflag[0][hh]) : "memory");
        asm volatile("red.relaxed.gpu.global.add.u32 [%0], 1;" ::"l"(&g_oflag[1][hh]) : "memory");
        TSTAMP(9 + r);
      }
      __syncwarp();
      if (W_PF == 1 && r + 2 < nheads) prefetch_w(r + 2);
    }
  }
}

__device__ __forceinline__ void att_s_role(uint32_t sb, uint8_t* smem, int w, int rank, int nheads, int warp_in_wg, int lane) {
  const AttBars B(sb + A_BAR);
  const uint32_t rk_empty = peer_addr(B.k_empty, rank ^ 1), rv_empty = peer_addr(B.v_empty, rank ^ 1);
  const uint32_t st_off = stsm_lane_off(warp_in_wg, lane);
  const float qscale = 0.08838834764831845f * 1.4426950408889634f;
  float acc[72], l[36];
#pragma unroll
  for (int i = 0; i < 36; i++) l[i] = 0.f;
  const uint32_t my_turn = B.turn + 8 * (w * 4 + warp_in_wg), other_turn = B.turn + 8 * ((w ^ 1) * 4 + warp_in_wg);
  uint32_t tph = w ^ 1;
  uint32_t kwph = 0, vwph = 0;
  int kuse = 0, vuse = 0;
  int n6 = w;
  uint32_t nph = 0;
  PH_DECL;
  for (int r = 0; r < nheads; r++) {
#define SSTAMP(k) do { if (w == 0 && warp_in_wg == 0 && lane == 0 && r < 6) CSTAMP(96 + 4 * r + (k)); } while (0)
    SSTAMP(0);
    {
      auto step = [&](int j, uint32_t& xa, uint32_t& wa, uint32_t& rel_x, uint32_t& rel_w, uint32_t& rel_wr) {
        if (j == 0 || j == 1 || j == 5 || j == 6) {
          const int h = (j == 1 || j == 6) ? 1 : 0;
          mbar_wait(B.xq_full + 8 * h, j >= 5 ? 1 : 0);
          xa = sb + A_Q + h * BT;
          rel_x = j < 2 ? B.xq_empty + 8 * h : 0;
        } else {
          const int sl = j == 7 ? 0 : j - 2;
          mbar_wait(B.x_full + 8 * sl, sl == 0 ? (j == 7 ? 1 : 0) : (r & 1));
          xa = sb + A_P + sl * BT;
          rel_x = B.b_empty + 8 * sl;
        }
        if (j < NWK) {
          const int sl = (kuse + j) % 3;
          mbar_wait(B.kw_full + 8 * sl, (kwph >> sl) & 1);
          kwph ^= 1u << sl;
          wa = sb + A_K + sl * 2 * AT + w * AT;
          rel_w = B.k_empty + 8 * sl; rel_wr = rk_empty + 8 * sl;
        } else {
          const int sl = (vuse + j - NWK) % 3;
          mbar_wait(B.vw_full + 8 * sl, (vwph >> sl) & 1);
          vwph ^= 1u << sl;
          wa = sb + A_V + sl * 2 * AT + w * AT;
          rel_w = B.v_empty + 8 * sl; rel_wr = rv_empty + 8 * sl;
        }
      };
      uint32_t xa, wa, rx, rw, rwr, prx, prw, prwr;
      if (r == 2 && warp_in_wg == 0 && lane == 0) DSTAMP(w * 10 + 8);
      step(0, xa, wa, prx, prw, prwr);
      if (r == 2 && warp_in_wg == 0 && lane == 0) DSTAMP(w * 10);
      PH(0);
      wg_fence();
      mma_kblock_mn<true>(acc, mkdesc(wa), mkdesc(xa));
      wg_commit();
#pragma unroll
      for (int j = 1; j < 8; j++) {
        step(j, xa, wa, rx, rw, rwr);
        if (r == 2 && warp_in_wg == 0 && lane == 0) DSTAMP(w * 10 + j);
        PH(0);
        wg_fence();
        mma_kblock_mn<false>(acc, mkdesc(wa), mkdesc(xa));
        wg_commit();
        wg_wait<1>();
        if (lane == 0) { mbar_arrive(prw); mbar_arrive_remote(prwr); if (prx) mbar_arrive(prx); }
        prx = rx; prw = rw; prwr = rwr;
        PH(1);
      }
      wg_wait<0>();
      if (lane == 0) { mbar_arrive(prw); mbar_arrive_remote(prwr); mbar_arrive(prx); mbar_arrive(B.qp_done); }
      SSTAMP(1);
      mbar_wait(B.qp_done, r & 1);
      store_tile_scaled(acc, sb + A_Q + w * BT + st_off, qscale);
      fence_async_smem();
      __syncwarp();
      if (lane == 0) mbar_arrive(B.q_ready);
      mbar_wait(B.q_ready, r & 1);
      SSTAMP(2);
      PH(2);
    }
#pragma unroll 1
    for (int t = w; t < 8; t += 2) {
      const int kslot = (kuse + NWK + t) % 3, slot = (t + 1) % 3;
      mbar_wait(B.k_full + 8 * n6, nph);
      n6 += 2;
      if (n6 >= 6) { n6 -= 6; nph ^= 1; }
      PH(3);
      {
        const uint64_t da = mkdesc(sb + A_K + kslot * 2 * AT), db = mkdesc(sb + A_Q);
        wg_fence();
        wgmma144<0, true>(acc, da, db);
#pragma unroll
        for (int kk = 1; kk < 8; kk++)
          wgmma144<0, false>(acc, da + (kk >> 2) * (AT >> 4) + (kk & 3) * 2, db + (kk >> 2) * (BT >> 4) + (kk & 3) * 2);
        wg_commit();
        wg_wait<0>();
      }
      if (lane == 0) {
        if (r + 1 < nheads || t < 5) { mbar_arrive2(B.k_empty + 8 * kslot); mbar_arrive2_remote(rk_empty + 8 * kslot); }
        if (t >= 6) mbar_arrive(B.s_done);
      }
      PH(4);
      mbar_wait(B.b_empty + 8 * slot, (((4 + t) / 3) & 1) ^ 1);
      mbar_wait(my_turn, tph);
      tph ^= 1;
      PH(5);
      const uint32_t pa = sb + A_P + slot * BT + st_off;
#pragma unroll
      for (int j = 0; j < 18; j += 2) {
        float* e = &acc[4 * j];
#pragma unroll
        for (int i = 0; i < 8; i++) e[i] = ex2(e[i]);
        l[2 * j] += e[0] + e[2];
        l[2 * j + 1] += e[1] + e[3];
        l[2 * j + 2] += e[4] + e[6];
        l[2 * j + 3] += e[5] + e[7];
        stsm_t4(pa + j * 1024, pack_bf16(e[0], e[1]), pack_bf16(e[2], e[3]), pack_bf16(e[4], e[5]), pack_bf16(e[6], e[7]));
      }
      if (lane == 0) mbar_arrive(other_turn);
      fence_async_smem();
      __syncwarp();
      if (lane == 0) mbar_arrive(B.p_full + 8 * slot);
      PH(6);
    }
    kuse = (kuse + NWK + 8) % 3;
    vuse = (vuse + 16 - NWK) % 3;
    SSTAMP(3);
    {
      float v[18], u[10];
      const bool b4 = lane & 16, b3 = lane & 8, b2 = lane & 4;
#pragma unroll
      for (int i = 0; i < 18; i++) {
        const float keep = b4 ? l[i + 18] : l[i], send = b4 ? l[i] : l[i + 18];
        v[i] = keep + __shfl_xor_sync(0xffffffffu, send, 16);
      }
#pragma unroll
      for (int i = 0; i < 9; i++) {
        const float keep = b3 ? v[i + 9] : v[i], send = b3 ? v[i] : v[i + 9];
        u[i] = keep + __shfl_xor_sync(0xffffffffu, send, 8);
      }
      u[9] = 0.f;
      float* lp = (float*)(smem + A_L) + (w * 4 + warp_in_wg) * SQ + 2 * (lane & 3);
      const int ibase = (b4 ? 18 : 0) + (b3 ? 9 : 0) + (b2 ? 5 : 0);
#pragma unroll
      for (int i = 0; i < 5; i++) {
        const float keep = b2 ? u[i + 5] : u[i], send = b2 ? u[i] : u[i + 5];
        const float sum = keep + __shfl_xor_sync(0xffffffffu, send, 4);
        const int idx = ibase + i;
        if (!(b2 && i == 4)) lp[8 * (idx >> 1) + (idx & 1)] = sum;
      }
      __syncwarp();
      if (lane == 0) mbar_arrive(B.l_ready);
#pragma unroll
      for (int i = 0; i < 36; i++) l[i] = 0.f;
      PH(7);
    }
  }
  PH_OUT(88 + 8 * w);
}

__device__ __forceinline__ void att_fallback(uint8_t* img, float* scr, const __nv_bfloat16* xb, const __nv_bfloat16* wq,
                                             const __nv_bfloat16* Kh, const __nv_bfloat16* Vh, int tid) {
  float* ps = scr;
  float* qs = scr + 512;
  float* red = scr + 640;
  const float qscale = 0.08838834764831845f * 1.4426950408889634f;
  for (int q = 0; q < SQ; q++) {
    float qa = 0.f;
    for (int k = 0; k < DM; k++) qa = fmaf(__bfloat162float(xb[q * DM + k]), __bfloat162float(wq[(size_t)k * (NH * DH) + tid]), qa);
    qs[tid] = __bfloat162float(__float2bfloat16(qa * qscale));
    named_bar(1, 128);
    float s[4], m = -INFINITY;
    for (int i = 0; i < 4; i++) {
      const __nv_bfloat16* kr = Kh + (size_t)(tid + 128 * i) * DH;
      float a = 0.f;
      for (int d = 0; d < DH; d++) a = fmaf(qs[d], __bfloat162float(kr[d]), a);
      s[i] = a;
      m = fmaxf(m, a);
    }
    for (int o = 16; o; o >>= 1) m = fmaxf(m, __shfl_xor_sync(0xffffffffu, m, o));
    if ((tid & 31) == 0) red[tid >> 5] = m;
    named_bar(1, 128);
    m = fmaxf(fmaxf(red[0], red[1]), fmaxf(red[2], red[3]));
    float sum = 0.f;
    for (int i = 0; i < 4; i++) {
      const float e = exp2f(s[i] - m);
      sum += e;
      ps[tid + 128 * i] = __bfloat162float(__float2bfloat16(e));
    }
    for (int o = 16; o; o >>= 1) sum += __shfl_xor_sync(0xffffffffu, sum, o);
    if ((tid & 31) == 0) red[4 + (tid >> 5)] = sum;
    named_bar(1, 128);
    sum = red[4] + red[5] + red[6] + red[7];
    float o = 0.f;
    for (int k = 0; k < SK; k++) o = fmaf(ps[k], __bfloat162float(Vh[(size_t)k * DH + tid]), o);
    const int off = (tid >> 6) * BT + q * 128 + (((((tid & 63) >> 3)) ^ (q & 7)) << 4) + (tid & 7) * 2;
    *(__nv_bfloat16*)(img + off) = __float2bfloat16(o / sum);
    named_bar(1, 128);
  }
}

__device__ __forceinline__ void att_o_epilogue(const Params& p, uint32_t sb, uint8_t* smem, const HeadList& hl, int r, int warp_in_wg,
                                               int lane, float (&acc0)[72], float (&acc1)[72]) {
  const AttBars B(sb + A_BAR);
  const int tid = warp_in_wg * 32 + lane;
  const uint32_t st_off = stsm_lane_off(warp_in_wg, lane);
  {
    EP(0);
    mbar_wait(B.l_ready, r & 1);
    float* lp = (float*)(smem + A_L);
    bool bad;
    {
      float l0 = 0.f, l1 = 1.f;
#pragma unroll
      for (int i = 0; i < 8; i++) l0 += lp[i * SQ + tid];
      if (tid < 16) {
        l1 = 0.f;
#pragma unroll
        for (int i = 0; i < 8; i++) l1 += lp[i * SQ + 128 + tid];
      }
      bad = !(l0 >= 5.4e-20f && l0 <= 1.8e19f && l1 >= 5.4e-20f && l1 <= 1.8e19f);
      lp[tid] = __fdividef(1.f, l0);
      if (tid < 16) lp[128 + tid] = __fdividef(1.f, l1);
    }
    named_bar(1, 128);
    mbar_wait(B.o_empty, (r & 1) ^ 1);
    EP(1);
    EP(3);
    const uint32_t img = sb + A_O + st_off;
    __nv_bfloat162 chk0 = __floats2bfloat162_rn(0.f, 0.f), chk1 = chk0, chk2 = chk0, chk3 = chk0;
    const __nv_bfloat162 zero2 = chk0;
    const float2* li2 = (const float2*)lp + (lane & 3);
    float2 sa = li2[0], sb2 = li2[4], sc = li2[8], sd = li2[12];
#pragma unroll
    for (int j = 0; j < 18; j += 2) {
      const float4 s = make_float4(sa.x, sa.y, sb2.x, sb2.y);
      sa = sc; sb2 = sd;
      if (j + 4 < 18) { sc = li2[4 * (j + 4)]; sd = li2[4 * (j + 5)]; }
      uint32_t a[4], c[4];
      a[0] = pack_bf16(acc0[4 * j] * s.x, acc0[4 * j + 1] * s.y);
      a[1] = pack_bf16(acc0[4 * j + 2] * s.x, acc0[4 * j + 3] * s.y);
      a[2] = pack_bf16(acc0[4 * j + 4] * s.z, acc0[4 * j + 5] * s.w);
      a[3] = pack_bf16(acc0[4 * j + 6] * s.z, acc0[4 * j + 7] * s.w);
      c[0] = pack_bf16(acc1[4 * j] * s.x, acc1[4 * j + 1] * s.y);
      c[1] = pack_bf16(acc1[4 * j + 2] * s.x, acc1[4 * j + 3] * s.y);
      c[2] = pack_bf16(acc1[4 * j + 4] * s.z, acc1[4 * j + 5] * s.w);
      c[3] = pack_bf16(acc1[4 * j + 6] * s.z, acc1[4 * j + 7] * s.w);
      stsm_t4(img + j * 1024, a[0], a[1], a[2], a[3]);
      stsm_t4(img + BT + j * 1024, c[0], c[1], c[2], c[3]);
      chk0 = __hfma2(*(const __nv_bfloat162*)&a[0], zero2, chk0); chk1 = __hfma2(*(const __nv_bfloat162*)&a[1], zero2, chk1);
      chk2 = __hfma2(*(const __nv_bfloat162*)&a[2], zero2, chk2); chk3 = __hfma2(*(const __nv_bfloat162*)&a[3], zero2, chk3);
      chk0 = __hfma2(*(const __nv_bfloat162*)&c[0], zero2, chk0); chk1 = __hfma2(*(const __nv_bfloat162*)&c[1], zero2, chk1);
      chk2 = __hfma2(*(const __nv_bfloat162*)&c[2], zero2, chk2); chk3 = __hfma2(*(const __nv_bfloat162*)&c[3], zero2, chk3);
    }
    const uint32_t chk = *(const uint32_t*)&chk0 | *(const uint32_t*)&chk1 | *(const uint32_t*)&chk2 | *(const uint32_t*)&chk3;
    bad = bad || ((chk & 0x7fff7fffu) != 0u);
    EP(4);
    uint32_t anybad;
    asm volatile("{\n.reg .pred p, q;\nsetp.ne.u32 p, %1, 0;\nbar.red.or.pred q, 1, 128, p;\nselp.u32 %0, 1, 0, q;\n}\n"
                 : "=r"(anybad)
                 : "r"((uint32_t)bad)
                 : "memory");
    EP(5);
    if (anybad) {
      const HeadId id = att_head(hl, r);
      const int blk = id.g >> 3;
      const size_t hoff = (size_t)((id.g & 7) * NH + id.h) * (SK * DH);
      att_fallback(smem + A_O, (float*)(smem + A_FB), p.X[blk] + (size_t)(id.g & 7) * SQ * DM, p.Wq[blk] + id.h * DH,
                   p.K[blk] + hoff, p.V[blk] + hoff, tid);
    }
    EP(6);
    fence_async_smem();
    __syncwarp();
    if (lane == 0) mbar_arrive(B.o_full);
    EP(7);
  }
}

__device__ __forceinline__ void op_producer(const Params& p, uint32_t sb, int g, int ch, int rank, int warp, int lane) {
  const uint32_t full = sb + O_BAR, empty = full + 8 * O_NS;
  if (warp == 1 && W_PF == 1) {
    for (int kb = 0; kb < 64; kb++) {
      if (kb >= 8) mbar_wait(empty + 8 * (kb & 3), ((kb - 8) >> 2) & 1);
      const uint8_t* src = (const uint8_t*)((g >> 3) ? p.Wo[1] : p.Wo[0]) + (size_t)(kb * 64 + (lane >> 2)) * (DM * 2) + ch * 512 + (lane & 3) * 128;
#pragma unroll
      for (int k = 0; k < 8; k++) lsu_prefetch(src + (size_t)k * 8 * (DM * 2));
    }
    return;
  }
  if (warp != 0 || lane != 0) return;
  const int blk = g >> 3;
  int slot = 0;
  uint32_t ph = 1;
  for (int kb = 0; kb < 64; kb++) {
    const int hh = g * NH + (kb >> 1);
    mbar_wait(empty + 8 * slot, ph);
    mbar_expect_tx(full + 8 * slot, O_STG);
    tma3d_mc(sb + slot * O_STG + rank * 2 * AT, &p.tmWo[blk], 0, kb * 64, ch * 4 + rank * 2, full + 8 * slot);
    if ((kb & 1) == 0) { flag_wait_reset(&g_oflag[ch][hh], 1); TSTAMP(1 + (kb >> 1)); }
    bulk_load(sb + slot * O_STG + 4 * AT, g_O + (size_t)hh * QIMG + (kb & 1) * BT, BT, full + 8 * slot);
    if (++slot == O_NS) { slot = 0; ph ^= 1; }
  }
}
__device__ __forceinline__ void op_store_tile(const Params& p, uint32_t sb, int g, int ch, int m, const float (&acc)[72], int warp_in_wg,
                                              int lane) {
  store_tile_scaled(acc, sb + m * BT + stsm_lane_off(warp_in_wg, lane), 1.f);
}
__device__ __forceinline__ void op_issue_store(const Params& p, uint32_t sb, int g, int ch, int m) {
  tma2d_store(&p.tmOut, sb + m * BT, (g >> 3) * DM + ch * 256 + m * 64, (g & 7) * SQ);
}
__device__ __forceinline__ void op_consumer1(const Params& p, uint32_t sb, int g, int ch, int rank, int m0, int warp_in_wg,
                                             int lane) {
  const uint32_t full = sb + O_BAR, empty = full + 8 * O_NS, rempty = peer_addr(empty, rank ^ 1);
  float acc0[72];
  int slot = 1, prev = 0;
  uint32_t ph = 0;
  mbar_wait(full, 0);
  wg_fence();
  mma_kblock_mn<true>(acc0, mkdesc(sb + m0 * AT), mkdesc(sb + 4 * AT));
  wg_commit();
  for (int kb = 1; kb < 64; kb++) {
    mbar_wait(full + 8 * slot, ph);
    wg_fence();
    mma_kblock_mn<false>(acc0, mkdesc(sb + slot * O_STG + m0 * AT), mkdesc(sb + slot * O_STG + 4 * AT));
    wg_commit();
    wg_wait<1>();
    if (lane == 0 && kb - 1 + O_NS < 64) { mbar_arrive(empty + 8 * prev); mbar_arrive_remote(rempty + 8 * prev); }
    prev = slot;
    if (++slot == O_NS) { slot = 0; ph ^= 1; }
  }
  wg_wait<0>();
  named_bar(2, 384);
  op_store_tile(p, sb, g, ch, m0, acc0, warp_in_wg, lane);
  fence_async_smem();
  named_bar(3 + m0, 128);
  if (warp_in_wg == 0 && lane == 0) {
    op_issue_store(p, sb, g, ch, m0);
    bulk_commit();
    bulk_wait_read();
  }
}

__device__ __forceinline__ void wg3_role(const Params& p, uint32_t sb, uint8_t* smem, bool is_att, int g, int idx, int rank,
                                         const HeadList& hl, int nheads, int warp_in_wg, int lane) {
  const AttBars B(sb + A_BAR);
  const uint32_t abase = is_att ? sb + A_V : sb + 2 * AT, astride = is_att ? 2 * AT : O_STG;
  const uint32_t bbase = is_att ? sb + A_P : sb + 4 * AT, bstride = is_att ? BT : O_STG;
  const uint32_t fullA = is_att ? B.v_full : sb + O_BAR, fullB = is_att ? B.p_full : sb + O_BAR;
  const uint32_t emptyA = is_att ? B.v_empty : sb + O_BAR + 8 * O_NS;
  const uint32_t remptyA = peer_addr(emptyA, rank ^ 1);
  const int ns = is_att ? 3 : O_NS;
  const int nouter = is_att ? nheads : 1, ninner = is_att ? 8 : 64;
  float acc0[72], acc1[72];
  PH_DECL;
  int slot = 0, prev = 0;
  uint32_t aph = 0;
  int bslot = 0;
  uint32_t bph = 0;
  for (int r = 0; r < nouter; r++) {
    if (is_att) {
      slot = (slot + 8 - NWK) % 3;
      bslot = 1;
    }
    {
      mbar_wait(fullA + 8 * slot, (aph >> slot) & 1);
      aph ^= 1u << slot;
      mbar_wait(fullB + 8 * bslot, (bph >> bslot) & 1);
      bph ^= 1u << bslot;
      wg_fence();
      mma_kblock_mn2<true>(acc0, acc1, mkdesc(abase + slot * astride), mkdesc(bbase + bslot * bstride));
      wg_commit();
      if (is_att) {
        wg_wait<0>();
        if (lane == 0) { mbar_arrive2(B.b_empty + 8 * bslot); mbar_arrive2(emptyA + 8 * slot); mbar_arrive2_remote(remptyA + 8 * slot); }
      }
      prev = slot;
      if (++slot == ns) slot = 0;
      if (++bslot == ns) bslot = 0;
    }
    for (int t = 1; t < ninner; t++) {
      PH(3);
      mbar_wait(fullA + 8 * slot, (aph >> slot) & 1);
      aph ^= 1u << slot;
      PH(0);
      mbar_wait(fullB + 8 * bslot, (bph >> bslot) & 1);
      bph ^= 1u << bslot;
      PH(1);
      wg_fence();
      mma_kblock_mn2<false>(acc0, acc1, mkdesc(abase + slot * astride), mkdesc(bbase + bslot * bstride));
      wg_commit();
      if (is_att) {
        wg_wait<0>();
        if (lane == 0) {
          mbar_arrive2(B.b_empty + 8 * bslot);
          if (r + 1 < nouter || t < 5) { mbar_arrive2(emptyA + 8 * slot); mbar_arrive2_remote(remptyA + 8 * slot); }
        }
      } else {
        wg_wait<1>();
        if (lane == 0 && t - 1 + O_NS < 64) { mbar_arrive(emptyA + 8 * prev); mbar_arrive_remote(remptyA + 8 * prev); }
      }
      PH(2);
      prev = slot;
      if (++slot == ns) slot = 0;
      if (++bslot == ns) bslot = 0;
    }
    wg_wait<0>();
    PH(4);
    if (is_att) {
      if (warp_in_wg == 0 && lane == 0) { CSTAMP(65 + r); TSTAMP(17 + r); }
      att_o_epilogue(p, sb, smem, hl, r, warp_in_wg, lane, acc0, acc1);
      if (warp_in_wg == 0 && lane == 0) CSTAMP(73 + r);
      PH(5);
    } else {
      named_bar(2, 384);
      op_store_tile(p, sb, g, idx, 2, acc0, warp_in_wg, lane);
      op_store_tile(p, sb, g, idx, 3, acc1, warp_in_wg, lane);
      fence_async_smem();
      named_bar(5, 128);
      if (warp_in_wg == 0 && lane == 0) {
        op_issue_store(p, sb, g, idx, 2);
        op_issue_store(p, sb, g, idx, 3);
        bulk_commit();
        bulk_wait_read();
        TSTAMP(40);
      }
    }
  }
  PH_OUT(104);
}

__global__ void __launch_bounds__(NTHREADS, 1) fused_attn_kernel(const __grid_constant__ Params p) {
  extern __shared__ __align__(1024) uint8_t smem[];
  const uint32_t sb = smem_u32(smem);
  const int warp = __shfl_sync(0xffffffffu, threadIdx.x >> 5, 0), lane = threadIdx.x & 31;
  const int wg = warp >> 2, warp_in_wg = warp & 3;
  const int rank = blockIdx.x & 1;
  const int npair = gridDim.x >> 1, ps = npair >> 1;
  volatile int* s_slot = (volatile int*)(smem + SMEM_BYTES - 16);
  if (threadIdx.x == 0 && rank == 0) {
    int slot = blockIdx.x >> 1;
    if (p.sidemap) {
      uint32_t v, t0, t1, best = 0xffffffffu;
      for (int i = 0; i < 2; i++) {
        asm volatile("mov.u32 %0, %clock;" : "=r"(t0)::"memory");
        asm volatile("atom.global.add.u32 %0, [%1], 0;" : "=r"(v) : "l"(&g_probe[0]) : "memory");
        asm volatile("{\n.reg .pred p;\nsetp.ne.u32 p, %1, 0x7fffffff;\nmov.u32 %0, 0;\n@p mov.u32 %0, %clock;\n}\n" : "=r"(t1) : "r"(v) : "memory");
        best = min(best, t1 - t0);
      }
      const int side = best > SIDE_THR ? 1 : 0;
      const int t = (int)atomicAdd(&g_ticket[side][0], 1);
      slot = t < ps ? side * ps + t : (side ^ 1) * ps + ps - 1 - (t - ps);
    }
    s_slot[0] = slot;
    asm volatile("st.shared::cluster.s32 [%0], %1;" ::"r"(peer_addr(sb + SMEM_BYTES - 16, 1)), "r"(slot) : "memory");
  }
  asm volatile("barrier.cluster.arrive.release.aligned;\nbarrier.cluster.wait.acquire.aligned;" ::: "memory");
  const int pslot = s_slot[0];
  if (p.sidemap && threadIdx.x == 32 && rank == 0) {
    if (atomicAdd(&g_done, 1) == (uint32_t)npair - 1) { g_ticket[0][0] = 0; g_ticket[1][0] = 0; g_done = 0; __threadfence(); }
  }
  const int blk = pslot >= ps ? 1 : 0, pr = pslot - blk * ps;
  const bool is_op = (pr & 3) == 3 && pr < 32;
  int g = 0, idx = 0, nheads;
  HeadList hl;
  hl.blk = blk;
  hl.stride = p.natt;
  if (is_op) {
    const int m = pr >> 2;
    g = blk * 8 + 2 * (m >> 1) + rank;
    idx = m & 1;
    hl.i0 = NEARLY + 2 * m + rank;
    hl.i1 = 0;
    nheads = 1;
  } else {
    const int i = 2 * (pr - min((pr + 1) >> 2, 8)) + rank;
    idx = i;
    hl.i0 = i < NEARLY ? i : i + 16;
    hl.i1 = p.natt + 16 + i;
    nheads = 1 + (8 * NH - hl.i1 + p.natt - 1) / p.natt;
  }
  if (threadIdx.x == 0) { TSTAMP(0); CSTAMP(64); }

  if (threadIdx.x == 0) {
    const AttBars B(sb + A_BAR);
    for (int i = 0; i < 6; i++) mbar_init(B.k_full + 8 * i, 1);
    for (int i = 0; i < 3; i++) {
      mbar_init(B.kw_full + 8 * i, 1); mbar_init(B.k_empty + 8 * i, 16);
      mbar_init(B.vw_full + 8 * i, 1); mbar_init(B.v_full + 8 * i, 1); mbar_init(B.v_empty + 8 * i, 16);
      mbar_init(B.x_full + 8 * i, 1); mbar_init(B.p_full + 8 * i, 4); mbar_init(B.b_empty + 8 * i, 8);
    }
    for (int i = 0; i < 2; i++) { mbar_init(B.xq_full + 8 * i, 1); mbar_init(B.xq_empty + 8 * i, 8); }
    mbar_init(B.s_done, 8); mbar_init(B.qp_done, 8);
    mbar_init(B.q_ready, 8); mbar_init(B.l_ready, 8);
    mbar_init(B.o_full, 4); mbar_init(B.o_empty, 1);
    for (int i = 0; i < 8; i++) mbar_init(B.turn + 8 * i, 1);
    asm volatile("fence.mbarrier_init.release.cluster;" ::: "memory");
  }
  __syncthreads();
  asm volatile("barrier.cluster.arrive.release.aligned;\nbarrier.cluster.wait.acquire.aligned;" ::: "memory");

  auto switch_role = [&]() {
    __syncwarp();
    asm volatile("barrier.cluster.arrive.release;\nbarrier.cluster.wait.acquire;" ::: "memory");
    if (threadIdx.x == 0) {
      for (int i = 0; i < O_NS; i++) { mbar_init(sb + O_BAR + 8 * i, 1); mbar_init(sb + O_BAR + 8 * O_NS + 8 * i, 24); }
      asm volatile("fence.mbarrier_init.release.cluster;" ::: "memory");
    }
    __syncwarp();
    asm volatile("barrier.cluster.arrive.release;\nbarrier.cluster.wait.acquire;" ::: "memory");
  };
  const bool run_att = p.mode != 3, run_op = is_op && p.mode != 2;

  if (wg == 0) {
    asm volatile("setmaxnreg.dec.sync.aligned.u32 32;");
    if (run_att) att_producer(p, sb, hl, rank, nheads, warp, lane);
    if (run_op) {
      switch_role();
      op_producer(p, sb, g, idx, rank, warp, lane);
    }
  } else if (wg == 3) {
    asm volatile("setmaxnreg.inc.sync.aligned.u32 176;");
#pragma unroll 1
    for (int phase = run_att ? 0 : 1; phase < (run_op ? 2 : 1); phase++) {
      if (phase == 1) switch_role();
      wg3_role(p, sb, smem, phase == 0, g, idx, rank, hl, nheads, warp_in_wg, lane);
    }
  } else {
    asm volatile("setmaxnreg.inc.sync.aligned.u32 152;");
    if (run_att) {
      if (!is_op) { const long long t0 = clock64(); const long long d = STAG_EXPR; while (clock64() - t0 < d) __nanosleep(100); }
      att_s_role(sb, smem, wg - 1, rank, nheads, warp_in_wg, lane);
    }
    if (run_op) {
      switch_role();
      op_consumer1(p, sb, g, idx, rank, wg - 1, warp_in_wg, lane);
    }
  }
}

typedef CUresult (*EncodeFn)(CUtensorMap*, CUtensorMapDataType, cuuint32_t, void*, const cuuint64_t*, const cuuint64_t*,
                             const cuuint32_t*, const cuuint32_t*, CUtensorMapInterleave, CUtensorMapSwizzle,
                             CUtensorMapL2promotion, CUtensorMapFloatOOBfill);

void make_map(EncodeFn enc, CUtensorMap* m, const void* ptr, int rank, const cuuint64_t* dims, const cuuint64_t* strides,
              const cuuint32_t* box) {
  const cuuint32_t es[3] = {1, 1, 1};
  CUresult r = enc(m, CU_TENSOR_MAP_DATA_TYPE_BFLOAT16, rank, const_cast<void*>(ptr), dims, strides, box, es,
                   CU_TENSOR_MAP_INTERLEAVE_NONE, CU_TENSOR_MAP_SWIZZLE_128B, L2PROMO,
                   CU_TENSOR_MAP_FLOAT_OOB_FILL_NONE);
  (void)r;
}

}

#define KERNEL_MODE_SEQ 0

extern "C" void kernel_launch(void* const* d_in, const int* in_sizes, int n_in, void* d_out, int out_size) {
  (void)in_sizes; (void)n_in; (void)out_size;
  void* fn = nullptr;
  cudaDriverEntryPointQueryResult qr;
  cudaGetDriverEntryPoint("cuTensorMapEncodeTiled", &fn, cudaEnableDefault, &qr);
  EncodeFn enc = (EncodeFn)fn;
  Params p;
  for (int blk = 0; blk < 2; blk++) {
    const void* x = d_in[blk * 5 + 0];
    const void* k = d_in[blk * 5 + 1];
    const void* v = d_in[blk * 5 + 2];
    const void* wq = d_in[blk * 5 + 3];
    const void* wo = d_in[blk * 5 + 4];
    {
      const cuuint64_t dims[3] = {64, (cuuint64_t)NBATCH * NH * SK, 2}, str[2] = {256, 128};
      const cuuint32_t box[3] = {64, 64, 2};
      make_map(enc, &p.tmK[blk], k, 3, dims, str, box);
      make_map(enc, &p.tmV[blk], v, 3, dims, str, box);
    }
    {
      const cuuint64_t dims[3] = {64, DM, (cuuint64_t)NH * 2}, str[2] = {NH * DH * 2, 128};
      const cuuint32_t box[3] = {64, 64, 1};
      make_map(enc, &p.tmWq[blk], wq, 3, dims, str, box);
    }
    {
      const cuuint64_t dims[3] = {64, (cuuint64_t)NH * DH, 8}, str[2] = {DM * 2, 128};
      const cuuint32_t box[3] = {64, 64, 2};
      make_map(enc, &p.tmWo[blk], wo, 3, dims, str, box);
    }
    {
      const cuuint64_t dims[2] = {DM, (cuuint64_t)NBATCH * SQ}, str[1] = {DM * 2};
      const cuuint32_t box[2] = {64, SQ};
      make_map(enc, &p.tmX[blk], x, 2, dims, str, box);
    }
    p.K[blk] = (const __nv_bfloat16*)k;
    p.V[blk] = (const __nv_bfloat16*)v;
    p.X[blk] = (const __nv_bfloat16*)x;
    p.Wq[blk] = (const __nv_bfloat16*)wq;
    p.Wo[blk] = (const __nv_bfloat16*)wo;
  }
  {
    const cuuint64_t dims[2] = {2 * DM, (cuuint64_t)NBATCH * SQ}, str[1] = {2 * DM * 2};
    const cuuint32_t box[2] = {64, SQ};
    make_map(enc, &p.tmOut, d_out, 2, dims, str, box);
  }
  cudaFuncSetAttribute(fused_attn_kernel, cudaFuncAttributeMaxDynamicSharedMemorySize, SMEM_BYTES);
  int nsm = 132;
  cudaDeviceGetAttribute(&nsm, cudaDevAttrMultiProcessorCount, 0);
  if (nsm > 132) nsm = 132;
  nsm &= ~3;
  p.natt = nsm / 2 - 16;
  p.sidemap = 1;
  cudaLaunchConfig_t cfg = {};
  cfg.gridDim = dim3(nsm);
  cfg.blockDim = dim3(NTHREADS);
  cfg.dynamicSmemBytes = SMEM_BYTES;
  cfg.stream = cudaStreamPerThread;
  cudaLaunchAttribute at[1];
  at[0].id = cudaLaunchAttributeClusterDimension;
  at[0].val.clusterDim.x = 2;
  at[0].val.clusterDim.y = 1;
  at[0].val.clusterDim.z = 1;
  cfg.attrs = at;
  cfg.numAttrs = 1;
  p.mode = 0;
  cudaLaunchKernelEx(&cfg, fused_attn_kernel, p);
}
```

```cpp
#include <cuda_runtime.h>
#include <cuda_bf16.h>
#include <cuda.h>
#include <stdint.h>
#define DBG_SYNC(tag)

namespace {

constexpr int NBATCH = 8, SQ = 144, DM = 512, NH = 32, DH = 128, SK = 512;
constexpr int NGRP = 16;
constexpr int BT = SQ * 128;
constexpr int AT = 64 * 128;
constexpr int QIMG = 2 * BT;
constexpr int NTHREADS = 512;
constexpr int SMEM_BYTES = 232448;
constexpr uint32_t WAIT_LIMIT = 1u << 20;
#define PUB_FIRST
#define PLAIN_EX2
#define L2PROMO CU_TENSOR_MAP_L2_PROMOTION_NONE
#define SIDE_THR 430
#define STAG_EXPR (idx >= 40 ? (long long)STAGGER2 : (idx >= NEARLY ? (long long)STAGGER : 0ll))
#define STAGGER 12000
#define OPH 1
#define STAGGER2 STAGGER
#define OSPLIT 9
#define SPRIO 60
#define NEARLY 26
#define NWK 5
#define CLUSTER 2
#define W_PF 0
#define TURN_AT 16
#define PF_DIST 0

constexpr int A_Q = 0;
constexpr int A_O = A_Q + QIMG;
constexpr int A_P = A_O + QIMG;
constexpr int A_K = A_P + 3 * BT;
constexpr int A_V = A_K + 3 * 2 * AT;
constexpr int A_L = A_V + 3 * 2 * AT;
constexpr int A_FB = A_L + SQ * 4;
constexpr int A_BAR = A_L + 8 * SQ * 4;
static_assert(A_BAR % 8 == 0 && A_BAR + 416 <= SMEM_BYTES - 16 && A_FB + 648 * 4 <= A_BAR, "att smem");
constexpr int O_NS = 4;
constexpr int O_STG = 4 * AT + BT;
constexpr int O_BAR = O_NS * O_STG;
static_assert(O_STG % 1024 == 0 && O_BAR + 256 <= SMEM_BYTES, "op smem");

struct alignas(64) Params {
  CUtensorMap tmK[2], tmV[2], tmWq[2], tmWo[2], tmX[2], tmOut;
  const __nv_bfloat16* K[2];
  const __nv_bfloat16* V[2];
  const __nv_bfloat16* X[2];
  const __nv_bfloat16* Wq[2];
  const __nv_bfloat16* Wo[2];
  int natt;
  int sidemap;
  int mode;
};

__device__ uint8_t g_O[NGRP * NH * QIMG];
__device__ uint32_t g_oflag[2][NGRP * NH];
__device__ uint32_t g_probe[64];
__device__ uint32_t g_ticket[2][32];
__device__ uint32_t g_done;

#define TSTAMP(i)
#define CSTAMP(i)
#define DSTAMP(i)
#define PH_DECL
#define PH(i)
#define PH_OUT(base)
#define EP(i)
__device__ __forceinline__ uint32_t smem_u32(const void* p) { return (uint32_t)__cvta_generic_to_shared(p); }
__device__ __forceinline__ void mbar_init(uint32_t bar, uint32_t cnt) {
  asm volatile("mbarrier.init.shared::cta.b64 [%0], %1;" ::"r"(bar), "r"(cnt) : "memory");
}
__device__ __forceinline__ void mbar_expect_tx(uint32_t bar, uint32_t bytes) {
  asm volatile("mbarrier.arrive.expect_tx.shared::cta.b64 _, [%0], %1;" ::"r"(bar), "r"(bytes) : "memory");
}
__device__ __forceinline__ void mbar_arrive(uint32_t bar) {
  asm volatile("mbarrier.arrive.shared::cta.b64 _, [%0];" ::"r"(bar) : "memory");
}
__device__ __forceinline__ void mbar_arrive2(uint32_t bar) {
  asm volatile("mbarrier.arrive.shared::cta.b64 _, [%0], 2;" ::"r"(bar) : "memory");
}
__device__ __forceinline__ uint32_t peer_addr(uint32_t addr, uint32_t peer) {
  uint32_t r;
  asm volatile("mapa.shared::cluster.u32 %0, %1, %2;" : "=r"(r) : "r"(addr), "r"(peer));
  return r;
}
__device__ __forceinline__ void mbar_arrive_remote(uint32_t rbar) {
  asm volatile("mbarrier.arrive.shared::cluster.b64 _, [%0];" ::"r"(rbar) : "memory");
}
__device__ __forceinline__ void mbar_arrive2_remote(uint32_t rbar) {
  asm volatile("mbarrier.arrive.shared::cluster.b64 _, [%0], 2;" ::"r"(rbar) : "memory");
}
__device__ __forceinline__ bool mbar_try(uint32_t bar, uint32_t parity) {
  uint32_t ok;
  asm volatile(
      "{\n.reg .pred p;\nmbarrier.try_wait.parity.shared::cta.b64 p, [%1], %2;\nselp.u32 %0, 1, 0, p;\n}\n"
      : "=r"(ok)
      : "r"(bar), "r"(parity)
      : "memory");
  return ok;
}
__device__ __forceinline__ void mbar_wait(uint32_t bar, uint32_t parity) {
  if (mbar_try(bar, parity)) return;
  uint32_t n = 0;
  while (!mbar_try(bar, parity)) {
    if (++n > WAIT_LIMIT) __trap();
  }
}
__device__ __forceinline__ void fence_async_smem() { asm volatile("fence.proxy.async.shared::cta;" ::: "memory"); }
__device__ __forceinline__ void fence_async_all() { asm volatile("fence.proxy.async;" ::: "memory"); }
__device__ __forceinline__ void named_bar(int id, int n) { asm volatile("bar.sync %0, %1;" ::"r"(id), "r"(n) : "memory"); }

__device__ __forceinline__ uint64_t policy_evict_first() {
  uint64_t p;
  asm volatile("createpolicy.fractional.L2::evict_first.b64 %0, 1.0;" : "=l"(p));
  return p;
}
__device__ __forceinline__ void tma2d(uint32_t dst, const CUtensorMap* tm, int c0, int c1, uint32_t bar) {
  asm volatile("cp.async.bulk.tensor.2d.shared::cluster.global.mbarrier::complete_tx::bytes [%0], [%1, {%3, %4}], [%2];" ::"r"(dst),
               "l"(tm), "r"(bar), "r"(c0), "r"(c1)
               : "memory");
}
__device__ __forceinline__ void tma3d(uint32_t dst, const CUtensorMap* tm, int c0, int c1, int c2, uint32_t bar) {
  asm volatile("cp.async.bulk.tensor.3d.shared::cluster.global.mbarrier::complete_tx::bytes [%0], [%1, {%3, %4, %5}], [%2];" ::"r"(dst),
               "l"(tm), "r"(bar), "r"(c0), "r"(c1), "r"(c2)
               : "memory");
}
__device__ __forceinline__ void tma3d_mc(uint32_t dst, const CUtensorMap* tm, int c0, int c1, int c2, uint32_t bar) {
  asm volatile(
      "cp.async.bulk.tensor.3d.shared::cluster.global.mbarrier::complete_tx::bytes.multicast::cluster [%0], [%1, {%3, %4, %5}], [%2], %6;" ::"r"(dst),
      "l"(tm), "r"(bar), "r"(c0), "r"(c1), "r"(c2), "h"((uint16_t)3)
      : "memory");
}
__device__ __forceinline__ void tma3d_hint(uint32_t dst, const CUtensorMap* tm, int c0, int c1, int c2, uint32_t bar, uint64_t pol) {
  asm volatile(
      "cp.async.bulk.tensor.3d.shared::cluster.global.mbarrier::complete_tx::bytes.L2::cache_hint [%0], [%1, {%3, %4, %5}], [%2], %6;" ::"r"(dst),
      "l"(tm), "r"(bar), "r"(c0), "r"(c1), "r"(c2), "l"(pol)
      : "memory");
}
__device__ __forceinline__ void tma2d_prefetch(const CUtensorMap* tm, int c0, int c1) {
  asm volatile("cp.async.bulk.prefetch.tensor.2d.L2.global [%0, {%1, %2}];" ::"l"(tm), "r"(c0), "r"(c1) : "memory");
}
__device__ __forceinline__ void tma3d_prefetch(const CUtensorMap* tm, int c0, int c1, int c2) {
  asm volatile("cp.async.bulk.prefetch.tensor.3d.L2.global [%0, {%1, %2, %3}];" ::"l"(tm), "r"(c0), "r"(c1), "r"(c2) : "memory");
}
__device__ __forceinline__ void bulk_load(uint32_t dst, const void* src, uint32_t bytes, uint32_t bar) {
  asm volatile("cp.async.bulk.shared::cluster.global.mbarrier::complete_tx::bytes [%0], [%1], %2, [%3];" ::"r"(dst), "l"(src),
               "r"(bytes), "r"(bar)
               : "memory");
}
__device__ __forceinline__ void bulk_store(void* dst, uint32_t src, uint32_t bytes) {
  asm volatile("cp.async.bulk.global.shared::cta.bulk_group [%0], [%1], %2;" ::"l"(dst), "r"(src), "r"(bytes) : "memory");
}
__device__ __forceinline__ void tma2d_store(const CUtensorMap* tm, uint32_t src, int c0, int c1) {
  asm volatile("cp.async.bulk.tensor.2d.global.shared::cta.bulk_group [%0, {%2, %3}], [%1];" ::"l"(tm), "r"(src), "r"(c0), "r"(c1)
               : "memory");
}
__device__ __forceinline__ void bulk_commit() { asm volatile("cp.async.bulk.commit_group;" ::: "memory"); }
__device__ __forceinline__ void bulk_wait_read() { asm volatile("cp.async.bulk.wait_group.read 0;" ::: "memory"); }
__device__ __forceinline__ void bulk_wait_all() { asm volatile("cp.async.bulk.wait_group 0;" ::: "memory"); }
__device__ __forceinline__ void l2_prefetch(const void* src, uint32_t bytes, uint64_t pol) {
  asm volatile("cp.async.bulk.prefetch.L2.global.L2::cache_hint [%0], %1, %2;" ::"l"(src), "r"(bytes), "l"(pol) : "memory");
}
__device__ __forceinline__ void lsu_prefetch(const void* a) { asm volatile("prefetch.global.L2 [%0];" ::"l"(a)); }
__device__ __forceinline__ void flag_add_release(uint32_t* f) {
  asm volatile("red.release.gpu.global.add.u32 [%0], 1;" ::"l"(f) : "memory");
}
__device__ __forceinline__ void flag_wait_reset(uint32_t* f, uint32_t target) {
  uint32_t v, n = 0;
  while (true) {
    asm volatile("ld.acquire.gpu.global.u32 %0, [%1];" : "=r"(v) : "l"(f) : "memory");
    if (v >= target) break;
    if (++n > (1u << 24)) __trap();
    __nanosleep(20);
  }
  asm volatile("st.relaxed.gpu.global.u32 [%0], %1;" ::"l"(f), "r"(0u) : "memory");
  fence_async_all();
}

__device__ __forceinline__ void wg_fence() { asm volatile("wgmma.fence.sync.aligned;" ::: "memory"); }
__device__ __forceinline__ void wg_commit() { asm volatile("wgmma.commit_group.sync.aligned;" ::: "memory"); }
template <int N>
__device__ __forceinline__ void wg_wait() {
  asm volatile("wgmma.wait_group.sync.aligned %0;" ::"n"(N) : "memory");
}
typedef uint32_t desc_t;
__device__ __forceinline__ desc_t mkdesc(uint32_t addr) { return ((addr & 0x3FFFF) >> 4) | (1u << 16); }

#define ACC8(c, o) c(d[o]), c(d[o + 1]), c(d[o + 2]), c(d[o + 3]), c(d[o + 4]), c(d[o + 5]), c(d[o + 6]), c(d[o + 7])
#define ACC72(c) ACC8(c, 0), ACC8(c, 8), ACC8(c, 16), ACC8(c, 24), ACC8(c, 32), ACC8(c, 40), ACC8(c, 48), ACC8(c, 56), ACC8(c, 64)
#define WGMMA144_HEAD                                                                                                          \
  "wgmma.mma_async.sync.aligned.m64n144k16.f32.bf16.bf16 "                                                                     \
  "{%0, %1, %2, %3, %4, %5, %6, %7, %8, %9, %10, %11, %12, %13, %14, %15, %16, %17, %18, %19, %20, %21, %22, %23, "            \
  "%24, %25, %26, %27, %28, %29, %30, %31, %32, %33, %34, %35, %36, %37, %38, %39, %40, %41, %42, %43, %44, %45, %46, %47, "   \
  "%48, %49, %50, %51, %52, %53, %54, %55, %56, %57, %58, %59, %60, %61, %62, %63, %64, %65, %66, %67, %68, %69, %70, %71}, "
template <int TA, bool INIT>
__device__ __forceinline__ void wgmma144(float (&d)[72], desc_t da, desc_t db) {
  if constexpr (INIT) {
    asm volatile("{\n.reg .pred p;\n.reg .b64 da, db;\n.reg .b32 hi;\nmov.b32 hi, 0x40000040;\nmov.b64 da, {%72, hi};\n"
                 "mov.b64 db, {%73, hi};\nsetp.ne.b32 p, 0, 0;\n" WGMMA144_HEAD "da, db, p, 1, 1, %74, 0;\n}\n"
                 : ACC72("=f")
                 : "r"(da), "r"(db), "n"(TA));
  } else {
    asm volatile("{\n.reg .pred p;\n.reg .b64 da, db;\n.reg .b32 hi;\nmov.b32 hi, 0x40000040;\nmov.b64 da, {%72, hi};\n"
                 "mov.b64 db, {%73, hi};\nsetp.eq.b32 p, 0, 0;\n" WGMMA144_HEAD "da, db, p, 1, 1, %74, 0;\n}\n"
                 : ACC72("+f")
                 : "r"(da), "r"(db), "n"(TA));
  }
}
template <bool INIT>
__device__ __forceinline__ void mma_kblock_mn(float (&d)[72], desc_t da, desc_t db) {
  wgmma144<1, INIT>(d, da, db);
  wgmma144<1, false>(d, da + 128, db + 2);
  wgmma144<1, false>(d, da + 256, db + 4);
  wgmma144<1, false>(d, da + 384, db + 6);
}
template <bool INIT>
__device__ __forceinline__ void mma_kblock_mn2(float (&d0)[72], float (&d1)[72], desc_t da, desc_t db) {
  wgmma144<1, INIT>(d0, da, db);
  wgmma144<1, INIT>(d1, da + (AT >> 4), db);
#pragma unroll
  for (int kk = 1; kk < 4; kk++) {
    wgmma144<1, false>(d0, da + kk * 128, db + kk * 2);
    wgmma144<1, false>(d1, da + kk * 128 + (AT >> 4), db + kk * 2);
  }
}
__device__ __forceinline__ uint32_t pack_bf16(float lo, float hi) {
  uint32_t r;
  asm("cvt.rn.bf16x2.f32 %0, %1, %2;" : "=r"(r) : "f"(hi), "f"(lo));
  return r;
}
__device__ __forceinline__ void stsm_t4(uint32_t addr, uint32_t r0, uint32_t r1, uint32_t r2, uint32_t r3) {
  asm volatile("stmatrix.sync.aligned.m8n8.x4.trans.shared.b16 [%0], {%1, %2, %3, %4};" ::"r"(addr), "r"(r0), "r"(r1), "r"(r2),
               "r"(r3)
               : "memory");
}
__device__ __forceinline__ float ex2(float x) {
  float y;
  asm volatile("ex2.approx.ftz.f32 %0, %1;" : "=f"(y) : "f"(x));
  return y;
}
__device__ __forceinline__ void ex2x8_dep(float* x, uint32_t dep) {
  asm volatile(
      "{\n.reg .pred p;\nsetp.ne.u32 p, %8, 0xFFFFFFFF;\n"
      "@p ex2.approx.ftz.f32 %0, %0;\n@p ex2.approx.ftz.f32 %1, %1;\n@p ex2.approx.ftz.f32 %2, %2;\n@p ex2.approx.ftz.f32 %3, %3;\n"
      "@p ex2.approx.ftz.f32 %4, %4;\n@p ex2.approx.ftz.f32 %5, %5;\n@p ex2.approx.ftz.f32 %6, %6;\n@p ex2.approx.ftz.f32 %7, %7;\n}\n"
      : "+f"(x[0]), "+f"(x[1]), "+f"(x[2]), "+f"(x[3]), "+f"(x[4]), "+f"(x[5]), "+f"(x[6]), "+f"(x[7])
      : "r"(dep));
}
__device__ __forceinline__ uint32_t stsm_lane_off(int warp_in_wg, int lane) {
  int mi = lane >> 3, rr = lane & 7;
  return (uint32_t)(((mi >> 1) * 8 + rr) * 128 + (((2 * warp_in_wg + (mi & 1)) ^ rr) << 4));
}
__device__ __forceinline__ void store_tile_scaled(const float (&d)[72], uint32_t base, float s) {
#pragma unroll
  for (int j = 0; j < 18; j += 2) {
    stsm_t4(base + j * 1024, pack_bf16(d[4 * j] * s, d[4 * j + 1] * s), pack_bf16(d[4 * j + 2] * s, d[4 * j + 3] * s),
            pack_bf16(d[4 * j + 4] * s, d[4 * j + 5] * s), pack_bf16(d[4 * j + 6] * s, d[4 * j + 7] * s));
  }
}

struct AttBars {
  uint32_t kw_full, k_full, k_empty, vw_full, v_full, v_empty, x_full, p_full, b_empty, xq_full, xo_full, s_done, xo_empty, q_ready,
      l_ready, li_ready, o_full, o_empty, turn, xq_empty, xq_done;
  __device__ __forceinline__ AttBars(uint32_t b)
      : kw_full(b), k_full(b + 24), k_empty(b + 72), vw_full(b + 96), v_full(b + 120), v_empty(b + 144), x_full(b + 168),
        p_full(b + 192), b_empty(b + 216), xq_full(b + 240), xo_full(b + 256), s_done(b + 272), xo_empty(b + 280),
        q_ready(b + 288), l_ready(b + 296), li_ready(b + 304), o_full(b + 312), o_empty(b + 320), turn(b + 328), xq_empty(b + 304), xq_done(b + 392) {}
};
constexpr int ATT_BAR_BYTES = 400;
struct HeadList { int blk, i0, i2, full, stride; };
struct HeadId { int g, h; };
__device__ __forceinline__ HeadId att_head(const HeadList& hl, int r) {
  const int hi = r < OPH ? hl.i0 + r * hl.full : hl.i2 + (r - OPH) * hl.stride;
  return {hl.blk * 8 + (hi & 7), hi >> 3};
}
#define KVROW(id) ((((id).g & 7) * NH + (id).h) * SK)

__device__ __forceinline__ void att_producer(const Params& p, uint32_t sb, const HeadList& hl, int rank, int nheads, int warp,
                                             int lane) {
  const AttBars B(sb + A_BAR);
  if (lane != 0 && warp != 3) return;
  if (warp == 0 || warp == 1) {
    const bool isk = warp == 0;
    const int nw = isk ? 5 : 3;
    const uint32_t wlist = isk ? 0x65210u : 0x743u;
    const uint32_t base = sb + (isk ? A_K : A_V), empty = isk ? B.k_empty : B.v_empty, wfull = isk ? B.kw_full : B.vw_full;
    const uint64_t pol = policy_evict_first();
    int slot = 0, n6 = 0;
    uint32_t ph = 1;
    for (int r = 0; r < nheads; r++) {
      const HeadId id = att_head(hl, r);
      const int blk = id.g >> 3;
      for (int j = 0; j < nw + 8; j++) {
        const uint32_t dst = base + slot * 2 * AT;
        mbar_wait(empty + 8 * slot, ph);
        if (j < nw) {
          const int wj = (wlist >> (4 * j)) & 15;
          if (r == 2) DSTAMP(20 + wj);
          mbar_expect_tx(wfull + 8 * slot, 2 * AT);
          tma3d_mc(dst + rank * AT, &p.tmWq[blk], 0, wj * 64, id.h * 2 + rank, wfull + 8 * slot);
        } else {
          const uint32_t full = isk ? B.k_full + 8 * n6 : B.v_full + 8 * slot;
          mbar_expect_tx(full, 2 * AT);
          tma3d_hint(dst, isk ? &p.tmK[blk] : &p.tmV[blk], 0, KVROW(id) + (j - nw) * 64, 0, full, pol);
          if (++n6 == 6) n6 = 0;
        }
        if (++slot == 3) { slot = 0; ph ^= 1; }
      }
    }
  } else if (warp == 2) {
    int slot = 0;
    uint32_t ph = 1;
    for (int r = 0; r < nheads; r++) {
      const HeadId id = att_head(hl, r);
      const CUtensorMap* tm = &p.tmX[id.g >> 3];
      const int row = (id.g & 7) * SQ;
      auto load_x = [&](int j, uint32_t dst, uint32_t bar) {
        if (r == 2) DSTAMP(30 + j);
        mbar_expect_tx(bar, BT);
        tma2d(dst, tm, j * 64, row, bar);
      };
      auto load_b = [&](int j) {
        mbar_wait(B.b_empty + 8 * slot, ph);
        load_x(j, sb + A_P + slot * BT, B.x_full + 8 * slot);
        if (++slot == 3) { slot = 0; ph ^= 1; }
      };
      if (r == 0) {
        load_x(0, sb + A_O, B.xo_full);
        load_x(1, sb + A_O + BT, B.xo_full + 8);
      } else {
        mbar_wait(B.s_done, (r - 1) & 1);
      }
      load_x(2, sb + A_Q, B.xq_full);
      load_x(3, sb + A_Q + BT, B.xq_full + 8);
      load_b(4);
      load_b(5);
      mbar_wait(B.xq_empty, (r & 1));
      load_x(6, sb + A_Q, B.xq_full);
      load_b(7);
      mbar_wait(B.b_empty + 8 * slot, ph);
      if (++slot == 3) { slot = 0; ph ^= 1; }
      for (int t = 0; t < 8; t++) {
        mbar_wait(B.b_empty + 8 * slot, ph);
        if (++slot == 3) { slot = 0; ph ^= 1; }
      }
    }
  } else {
    auto prefetch_w = [&](int r) {
      const HeadId id = att_head(hl, r);
      const uint8_t* src = (const uint8_t*)((id.g >> 3) ? p.Wq[1] : p.Wq[0]) + (id.h * DH + rank * 64) * 2 + (size_t)lane * (NH * DH * 2);
#pragma unroll 4
      for (int k = 0; k < 16; k++) lsu_prefetch(src + (size_t)k * 32 * (NH * DH * 2));
    };
    auto load_x01 = [&](int r) {
      const HeadId nx = att_head(hl, r);
      for (int j = 0; j < 2; j++) {
        if (r == 2) DSTAMP(30 + j);
        mbar_expect_tx(B.xo_full + 8 * j, BT);
        tma2d(sb + A_O + j * BT, &p.tmX[nx.g >> 3], j * 64, (nx.g & 7) * SQ, B.xo_full + 8 * j);
      }
    };
    if (W_PF == 1 && nheads > 1) prefetch_w(1);
    if (lane == 0 && nheads > 1) {
      mbar_wait(B.xo_empty, 0);
      load_x01(1);
    }
    for (int r = 0; r < nheads; r++) {
      if (lane == 0) {
        const HeadId id = att_head(hl, r);
        const int hh = id.g * NH + id.h;
        mbar_wait(B.o_full, r & 1);
        if (r < 2) DSTAMP(40 + 0 + 4 * r + 2);
#pragma unroll
        for (int c = 0; c < OSPLIT; c++) bulk_store(g_O + (size_t)hh * QIMG + c * (QIMG / OSPLIT), sb + A_O + c * (QIMG / OSPLIT), QIMG / OSPLIT);
        bulk_commit();
        bulk_wait_read();
        if (r < 2) DSTAMP(40 + 1 + 4 * r + 2);
        mbar_arrive(B.o_empty);
        if (r + 2 < nheads) load_x01(r + 2);
        bulk_wait_all();
        if (r < 2) DSTAMP(40 + 2 + 4 * r + 2);
        asm volatile("red.relaxed.gpu.global.add.u32 [%0], 1;" ::"l"(&g_oflag[0][hh]) : "memory");
        asm volatile("red.relaxed.gpu.global.add.u32 [%0], 1;" ::"l"(&g_oflag[1][hh]) : "memory");
        if (r < 2) DSTAMP(40 + 3 + 4 * r + 2);
        TSTAMP(9 + r);
      }
      __syncwarp();
      if (W_PF == 1 && r + 2 < nheads) prefetch_w(r + 2);
    }
  }
}

__device__ __forceinline__ void att_s_role(uint32_t sb, uint8_t* smem, int w, int rank, int nheads, int warp_in_wg, int lane) {
  const AttBars B(sb + A_BAR);
  const uint32_t rk_empty = peer_addr(B.k_empty, rank ^ 1), rv_empty = peer_addr(B.v_empty, rank ^ 1);
  const uint32_t st_off = stsm_lane_off(warp_in_wg, lane);
  const float qscale = 0.08838834764831845f * 1.4426950408889634f;
  float acc[72], l[36];
#pragma unroll
  for (int i = 0; i < 36; i++) l[i] = 0.f;
  const uint32_t my_turn = B.turn + 8 * (w * 4 + warp_in_wg), other_turn = B.turn + 8 * ((w ^ 1) * 4 + warp_in_wg);
  uint32_t tph = w ^ 1;
  uint32_t kwph = 0, vwph = 0;
  int kuse = 0, vuse = 0;
  int n6 = w;
  uint32_t nph = 0;
  auto flush_l = [&]() {
      float v[18], u[10];
      const bool b4 = lane & 16, b3 = lane & 8, b2 = lane & 4;
#pragma unroll
      for (int i = 0; i < 18; i++) {
        const float keep = b4 ? l[i + 18] : l[i], send = b4 ? l[i] : l[i + 18];
        v[i] = keep + __shfl_xor_sync(0xffffffffu, send, 16);
      }
#pragma unroll
      for (int i = 0; i < 9; i++) {
        const float keep = b3 ? v[i + 9] : v[i], send = b3 ? v[i] : v[i + 9];
        u[i] = keep + __shfl_xor_sync(0xffffffffu, send, 8);
      }
      u[9] = 0.f;
      float* lp = (float*)(smem + A_L) + (w * 4 + warp_in_wg) * SQ + 2 * (lane & 3);
      const int ibase = (b4 ? 18 : 0) + (b3 ? 9 : 0) + (b2 ? 5 : 0);
#pragma unroll
      for (int i = 0; i < 5; i++) {
        const float keep = b2 ? u[i + 5] : u[i], send = b2 ? u[i] : u[i + 5];
        const float sum = keep + __shfl_xor_sync(0xffffffffu, send, 4);
        const int idx = ibase + i;
        if (!(b2 && i == 4)) lp[8 * (idx >> 1) + (idx & 1)] = sum;
      }
      __syncwarp();
      if (lane == 0) mbar_arrive(B.l_ready);
#pragma unroll
      for (int i = 0; i < 36; i++) l[i] = 0.f;
  };
  PH_DECL;
  for (int r = 0; r < nheads; r++) {
#define SSTAMP(k) do { if (w == 0 && warp_in_wg == 0 && lane == 0 && r < 6) CSTAMP(96 + 4 * r + (k)); } while (0)
    SSTAMP(0);
    {
      auto step = [&](int j, uint32_t& xa, uint32_t& wa, uint32_t& rel_x, uint32_t& rel_w, uint32_t& rel_wr) {
        if (j < 2) {
          mbar_wait(B.xo_full + 8 * j, r & 1);
          xa = sb + A_O + j * BT;
          rel_x = B.xo_empty;
        } else if (j < 4 || j == 6) {
          const int h = j == 3 ? 1 : 0;
          mbar_wait(B.xq_full + 8 * h, h ? (r & 1) : (j == 6 ? 1 : 0));
          xa = sb + A_Q + h * BT;
          rel_x = j == 2 ? B.xq_empty : (j == 6 ? B.xq_done : 0);
        } else {
          const int sl = j == 7 ? 2 : j - 4;
          mbar_wait(B.x_full + 8 * sl, r & 1);
          xa = sb + A_P + sl * BT;
          rel_x = B.b_empty + 8 * sl;
        }
        if (j < 3 || j == 5 || j == 6) {
          const int sl = (kuse + (j < 3 ? j : j - 2)) % 3;
          mbar_wait(B.kw_full + 8 * sl, (kwph >> sl) & 1);
          kwph ^= 1u << sl;
          wa = sb + A_K + sl * 2 * AT + w * AT;
          rel_w = B.k_empty + 8 * sl; rel_wr = rk_empty + 8 * sl;
        } else {
          const int sl = (vuse + (j == 7 ? 2 : j - 3)) % 3;
          mbar_wait(B.vw_full + 8 * sl, (vwph >> sl) & 1);
          vwph ^= 1u << sl;
          wa = sb + A_V + sl * 2 * AT + w * AT;
          rel_w = B.v_empty + 8 * sl; rel_wr = rv_empty + 8 * sl;
        }
      };
      uint32_t xa, wa, rx, rw, rwr, prx, prw, prwr;
      if (r == 2 && warp_in_wg == 0 && lane == 0) DSTAMP(w * 10 + 8);
      step(0, xa, wa, prx, prw, prwr);
      if (r == 2 && warp_in_wg == 0 && lane == 0) DSTAMP(w * 10);
      PH(0);
      wg_fence();
      mma_kblock_mn<true>(acc, mkdesc(wa), mkdesc(xa));
      wg_commit();
      if (r > 1 && w == 1) flush_l();
#pragma unroll
      for (int j = 1; j < 8; j++) {
        step(j, xa, wa, rx, rw, rwr);
        if (r == 2 && warp_in_wg == 0 && lane == 0) DSTAMP(w * 10 + j);
        PH(0);
        wg_fence();
        mma_kblock_mn<false>(acc, mkdesc(wa), mkdesc(xa));
        wg_commit();
        wg_wait<1>();
        if (lane == 0) { mbar_arrive(prw); mbar_arrive_remote(prwr); if (prx) mbar_arrive(prx); }
        prx = rx; prw = rw; prwr = rwr;
        PH(1);
      }
      wg_wait<0>();
      if (lane == 0) { mbar_arrive(prw); mbar_arrive_remote(prwr); mbar_arrive(prx); mbar_arrive(B.b_empty);   }
      SSTAMP(1);
      mbar_wait(B.xq_done, r & 1);
      store_tile_scaled(acc, sb + A_Q + w * BT + st_off, qscale);
      fence_async_smem();
      __syncwarp();
      if (lane == 0) mbar_arrive(B.q_ready);
      mbar_wait(B.q_ready, r & 1);
      SSTAMP(2);
      PH(2);
    }
#pragma unroll 1
    for (int t = w; t < 8; t += 2) {
      const int kslot = (kuse + 5 + t) % 3, slot = (t + 1) % 3;
      mbar_wait(B.k_full + 8 * n6, nph);
      n6 += 2;
      if (n6 >= 6) { n6 -= 6; nph ^= 1; }
      PH(3);
      {
        const desc_t da = mkdesc(sb + A_K + kslot * 2 * AT), db = mkdesc(sb + A_Q);
        wg_fence();
        wgmma144<0, true>(acc, da, db);
#pragma unroll
        for (int kk = 1; kk < 8; kk++)
          wgmma144<0, false>(acc, da + (kk >> 2) * (AT >> 4) + (kk & 3) * 2, db + (kk >> 2) * (BT >> 4) + (kk & 3) * 2);
        wg_commit();
        wg_wait<0>();
      }
      if (lane == 0) {
        if (warp_in_wg == 0) *(volatile uint32_t*)(smem + A_BAR + 408 + 4 * w) = 4 * r + (t >> 1) + 1;
        if (r + 1 < nheads || t < 5) { mbar_arrive2(B.k_empty + 8 * kslot); mbar_arrive2_remote(rk_empty + 8 * kslot); }
        if (t >= 6) mbar_arrive(B.s_done);
      }
      PH(4);
      mbar_wait(B.b_empty + 8 * slot, (((4 + t) / 3) & 1) ^ 1);
      mbar_wait(my_turn, tph);
      tph ^= 1;
      PH(5);
      const uint32_t pa = sb + A_P + slot * BT + st_off;
#pragma unroll
      for (int j = 0; j < 18; j += 2) {
        float* e = &acc[4 * j];
#pragma unroll
        for (int i = 0; i < 8; i++) e[i] = ex2(e[i]);
        l[2 * j] += e[0] + e[2];
        l[2 * j + 1] += e[1] + e[3];
        l[2 * j + 2] += e[4] + e[6];
        l[2 * j + 3] += e[5] + e[7];
        stsm_t4(pa + j * 1024, pack_bf16(e[0], e[1]), pack_bf16(e[2], e[3]), pack_bf16(e[4], e[5]), pack_bf16(e[6], e[7]));
      }
      if (lane == 0) mbar_arrive(other_turn);
      fence_async_smem();
      __syncwarp();
      if (lane == 0) mbar_arrive(B.p_full + 8 * slot);
      PH(6);
    }
    kuse = (kuse + 13) % 3;
    vuse = (vuse + 11) % 3;
    SSTAMP(3);
    if (w == 0 || r == 0) flush_l();
  }
  if (w == 1 && nheads > 1) flush_l();
  PH_OUT(88 + 8 * w);
}

__device__ __forceinline__ void att_fallback(uint8_t* img, float* scr, const __nv_bfloat16* xb, const __nv_bfloat16* wq,
                                             const __nv_bfloat16* Kh, const __nv_bfloat16* Vh, int tid) {
  float* ps = scr;
  float* qs = scr + 512;
  float* red = scr + 640;
  const float qscale = 0.08838834764831845f * 1.4426950408889634f;
  for (int q = 0; q < SQ; q++) {
    float qa = 0.f;
    for (int k = 0; k < DM; k++) qa = fmaf(__bfloat162float(xb[q * DM + k]), __bfloat162float(wq[(size_t)k * (NH * DH) + tid]), qa);
    qs[tid] = __bfloat162float(__float2bfloat16(qa * qscale));
    named_bar(1, 128);
    float s[4], m = -INFINITY;
    for (int i = 0; i < 4; i++) {
      const __nv_bfloat16* kr = Kh + (size_t)(tid + 128 * i) * DH;
      float a = 0.f;
      for (int d = 0; d < DH; d++) a = fmaf(qs[d], __bfloat162float(kr[d]), a);
      s[i] = a;
      m = fmaxf(m, a);
    }
    for (int o = 16; o; o >>= 1) m = fmaxf(m, __shfl_xor_sync(0xffffffffu, m, o));
    if ((tid & 31) == 0) red[tid >> 5] = m;
    named_bar(1, 128);
    m = fmaxf(fmaxf(red[0], red[1]), fmaxf(red[2], red[3]));
    float sum = 0.f;
    for (int i = 0; i < 4; i++) {
      const float e = exp2f(s[i] - m);
      sum += e;
      ps[tid + 128 * i] = __bfloat162float(__float2bfloat16(e));
    }
    for (int o = 16; o; o >>= 1) sum += __shfl_xor_sync(0xffffffffu, sum, o);
    if ((tid & 31) == 0) red[4 + (tid >> 5)] = sum;
    named_bar(1, 128);
    sum = red[4] + red[5] + red[6] + red[7];
    float o = 0.f;
    for (int k = 0; k < SK; k++) o = fmaf(ps[k], __bfloat162float(Vh[(size_t)k * DH + tid]), o);
    const int off = (tid >> 6) * BT + q * 128 + (((((tid & 63) >> 3)) ^ (q & 7)) << 4) + (tid & 7) * 2;
    *(__nv_bfloat16*)(img + off) = __float2bfloat16(o / sum);
    named_bar(1, 128);
  }
}

__device__ __forceinline__ void att_o_epilogue(const Params& p, uint32_t sb, uint8_t* smem, const HeadList& hl, int r, int nheads,
                                               int warp_in_wg,
                                               int lane, float (&acc0)[72], float (&acc1)[72]) {
  const AttBars B(sb + A_BAR);
  const int tid = warp_in_wg * 32 + lane;
  const uint32_t st_off = stsm_lane_off(warp_in_wg, lane);
  {
    EP(0);
    mbar_wait(B.l_ready, r & 1);
    float* lp = (float*)(smem + A_L);
    bool bad;
    {
      float l0 = 0.f, l1 = 1.f;
#pragma unroll
      for (int i = 0; i < 8; i++) l0 += lp[i * SQ + tid];
      if (tid < 16) {
        l1 = 0.f;
#pragma unroll
        for (int i = 0; i < 8; i++) l1 += lp[i * SQ + 128 + tid];
      }
      bad = !(l0 >= 5.4e-20f && l0 <= 1.8e19f && l1 >= 5.4e-20f && l1 <= 1.8e19f);
      lp[tid] = __fdividef(1.f, l0);
      if (tid < 16) lp[128 + tid] = __fdividef(1.f, l1);
    }
    named_bar(1, 128);
    EP(1);
    const uint32_t img = sb + A_O + st_off;
    __nv_bfloat162 chk0 = __floats2bfloat162_rn(0.f, 0.f), chk1 = chk0, chk2 = chk0, chk3 = chk0;
    const __nv_bfloat162 zero2 = chk0;
    const float2* li2 = (const float2*)lp + (lane & 3);
    float2 sa = li2[0], sb2 = li2[4], sc = li2[8], sd = li2[12];
    uint32_t a[36], c[36];
#pragma unroll
    for (int j = 0; j < 18; j += 2) {
      const float4 s = make_float4(sa.x, sa.y, sb2.x, sb2.y);
      sa = sc; sb2 = sd;
      if (j + 4 < 18) { sc = li2[4 * (j + 4)]; sd = li2[4 * (j + 5)]; }
      a[2 * j] = pack_bf16(acc0[4 * j] * s.x, acc0[4 * j + 1] * s.y);
      a[2 * j + 1] = pack_bf16(acc0[4 * j + 2] * s.x, acc0[4 * j + 3] * s.y);
      a[2 * j + 2] = pack_bf16(acc0[4 * j + 4] * s.z, acc0[4 * j + 5] * s.w);
      a[2 * j + 3] = pack_bf16(acc0[4 * j + 6] * s.z, acc0[4 * j + 7] * s.w);
      c[2 * j] = pack_bf16(acc1[4 * j] * s.x, acc1[4 * j + 1] * s.y);
      c[2 * j + 1] = pack_bf16(acc1[4 * j + 2] * s.x, acc1[4 * j + 3] * s.y);
      c[2 * j + 2] = pack_bf16(acc1[4 * j + 4] * s.z, acc1[4 * j + 5] * s.w);
      c[2 * j + 3] = pack_bf16(acc1[4 * j + 6] * s.z, acc1[4 * j + 7] * s.w);
      chk0 = __hfma2(*(const __nv_bfloat162*)&a[2 * j], zero2, chk0); chk0 = __hfma2(*(const __nv_bfloat162*)&a[2 * j + 1], zero2, chk0);
      chk1 = __hfma2(*(const __nv_bfloat162*)&a[2 * j + 2], zero2, chk1); chk2 = __hfma2(*(const __nv_bfloat162*)&a[2 * j + 3], zero2, chk2);
      chk3 = __hfma2(*(const __nv_bfloat162*)&c[2 * j], zero2, chk3); chk1 = __hfma2(*(const __nv_bfloat162*)&c[2 * j + 1], zero2, chk1);
      chk2 = __hfma2(*(const __nv_bfloat162*)&c[2 * j + 2], zero2, chk2); chk3 = __hfma2(*(const __nv_bfloat162*)&c[2 * j + 3], zero2, chk3);
    }
    if (r + 1 < nheads) mbar_wait(B.xo_empty, (r + 1) & 1);
    else mbar_wait(B.o_empty, (r & 1) ^ 1);
#pragma unroll
    for (int j = 0; j < 18; j += 2) {
      stsm_t4(img + j * 1024, a[2 * j], a[2 * j + 1], a[2 * j + 2], a[2 * j + 3]);
      stsm_t4(img + BT + j * 1024, c[2 * j], c[2 * j + 1], c[2 * j + 2], c[2 * j + 3]);
    }
    const uint32_t chk = *(const uint32_t*)&chk0 | *(const uint32_t*)&chk1 | *(const uint32_t*)&chk2 | *(const uint32_t*)&chk3;
    bad = bad || ((chk & 0x7fff7fffu) != 0u);
    EP(4);
    uint32_t anybad;
    asm volatile("{\n.reg .pred p, q;\nsetp.ne.u32 p, %1, 0;\nbar.red.or.pred q, 1, 128, p;\nselp.u32 %0, 1, 0, q;\n}\n"
                 : "=r"(anybad)
                 : "r"((uint32_t)bad)
                 : "memory");
    EP(5);
    if (anybad) {
      const HeadId id = att_head(hl, r);
      const int blk = id.g >> 3;
      const size_t hoff = (size_t)((id.g & 7) * NH + id.h) * (SK * DH);
      att_fallback(smem + A_O, (float*)(smem + A_FB), p.X[blk] + (size_t)(id.g & 7) * SQ * DM, p.Wq[blk] + id.h * DH,
                   p.K[blk] + hoff, p.V[blk] + hoff, tid);
    }
    EP(6);
    fence_async_smem();
    __syncwarp();
    if (lane == 0) mbar_arrive(B.o_full);
    EP(7);
  }
}

__device__ __forceinline__ void op_producer(const Params& p, uint32_t sb, uint8_t* smem, int g, int ch, int rank, int warp, int lane) {
  const uint32_t full = sb + O_BAR, empty = full + 8 * O_NS;
  volatile uint32_t* nready = (volatile uint32_t*)(smem + O_BAR + 128);
  if (warp == 1) {
    uint32_t* f = &g_oflag[ch][g * NH + lane];
    bool seen = false;
    uint32_t cnt = 0, n = 0;
    while (cnt < NH) {
      if (!seen) {
        uint32_t v;
        asm volatile("ld.acquire.gpu.global.u32 %0, [%1];" : "=r"(v) : "l"(f) : "memory");
        if (v) {
          seen = true;
          asm volatile("st.relaxed.gpu.global.u32 [%0], %1;" ::"l"(f), "r"(0u) : "memory");
        }
      }
      const uint32_t m = __ballot_sync(0xffffffffu, seen);
      const uint32_t c = m == 0xffffffffu ? 32u : (uint32_t)(__ffs(~m) - 1);
      if (c != cnt) {
        cnt = c;
        __syncwarp();
        if (lane == 0) {
          asm volatile("fence.acq_rel.cta;" ::: "memory");
          *nready = c;
        }
      } else {
        if (++n > (1u << 24)) __trap();
        __nanosleep(40);
      }
    }
    return;
  }
  if (warp != 0 || lane != 0) return;
  const int blk = g >> 3;
  int slot = 0;
  uint32_t ph = 1, have = 0;
  for (int kb = 0; kb < 64; kb++) {
    const int hh = g * NH + (kb >> 1);
    mbar_wait(empty + 8 * slot, ph);
    if (kb >= 40 && kb < 48) DSTAMP(44 + kb - 40);
    mbar_expect_tx(full + 8 * slot, O_STG);
    tma3d_mc(sb + slot * O_STG + rank * 2 * AT, &p.tmWo[blk], 0, kb * 64, ch * 4 + rank * 2, full + 8 * slot);
    if ((uint32_t)(kb >> 1) >= have) {
      uint32_t n = 0;
      while ((have = *nready) <= (uint32_t)(kb >> 1)) {
        if (++n > (1u << 26)) __trap();
      }
      asm volatile("fence.acq_rel.cta;" ::: "memory");
    }
    if ((kb & 1) == 0) TSTAMP(1 + (kb >> 1));
    bulk_load(sb + slot * O_STG + 4 * AT, g_O + (size_t)hh * QIMG + (kb & 1) * BT, BT, full + 8 * slot);
    if (++slot == O_NS) { slot = 0; ph ^= 1; }
  }
}
__device__ __forceinline__ void op_store_tile(const Params& p, uint32_t sb, int g, int ch, int m, const float (&acc)[72], int warp_in_wg,
                                              int lane) {
  store_tile_scaled(acc, sb + m * BT + stsm_lane_off(warp_in_wg, lane), 1.f);
}
__device__ __forceinline__ void op_issue_store(const Params& p, uint32_t sb, int g, int ch, int m) {
  tma2d_store(&p.tmOut, sb + m * BT, (g >> 3) * DM + ch * 256 + m * 64, (g & 7) * SQ);
}
__device__ __forceinline__ void op_consumer1(const Params& p, uint32_t sb, int g, int ch, int rank, int m0, int warp_in_wg,
                                             int lane) {
  const uint32_t full = sb + O_BAR, empty = full + 8 * O_NS, rempty = peer_addr(empty, rank ^ 1);
  float acc0[72];
  int slot = 1, prev = 0;
  uint32_t ph = 0;
  mbar_wait(full, 0);
  wg_fence();
  mma_kblock_mn<true>(acc0, mkdesc(sb + m0 * AT), mkdesc(sb + 4 * AT));
  wg_commit();
  for (int kb = 1; kb < 64; kb++) {
    mbar_wait(full + 8 * slot, ph);
    if (m0 == 0 && warp_in_wg == 0 && lane == 0 && kb >= 40 && kb < 48) DSTAMP(0 + kb - 40);
    wg_fence();
    mma_kblock_mn<false>(acc0, mkdesc(sb + slot * O_STG + m0 * AT), mkdesc(sb + slot * O_STG + 4 * AT));
    wg_commit();
    wg_wait<1>();
    if (lane == 0 && kb - 1 + O_NS < 64) { mbar_arrive(empty + 8 * prev); mbar_arrive_remote(rempty + 8 * prev); }
    prev = slot;
    if (++slot == O_NS) { slot = 0; ph ^= 1; }
  }
  wg_wait<0>();
  named_bar(2, 384);
  op_store_tile(p, sb, g, ch, m0, acc0, warp_in_wg, lane);
  fence_async_smem();
  named_bar(3 + m0, 128);
  if (warp_in_wg == 0 && lane == 0) {
    op_issue_store(p, sb, g, ch, m0);
    bulk_commit();
    bulk_wait_read();
  }
}

__device__ __forceinline__ void wg3_role(const Params& p, uint32_t sb, uint8_t* smem, bool is_att, int g, int idx, int rank,
                                         const HeadList& hl, int nheads, int warp_in_wg, int lane, float (&acc0)[72],
                                         float (&acc1)[72]) {
  if (is_att) {
    const AttBars B(sb + A_BAR);
    const uint32_t rv_empty = peer_addr(B.v_empty, rank ^ 1);
    PH_DECL;
    int slot = 0;
    uint32_t aph = 0;
    uint32_t bph = 0;
    auto sprio = [&](int r, int t) {
      volatile uint32_t* c = (volatile uint32_t*)(smem + A_BAR + 408 + 4 * (t & 1));
      const uint32_t need = 4 * r + ((t + 2) >> 1) + 1;
      uint32_t n = 0;
      while (*c < need && ++n < SPRIO) { }
    };
    for (int r = 0; r < nheads; r++) {
      int bslot = 1;
      {
        mbar_wait(B.v_full + 8 * slot, (aph >> slot) & 1);
        aph ^= 1u << slot;
        mbar_wait(B.p_full + 8 * bslot, (bph >> bslot) & 1);
        bph ^= 1u << bslot;
        sprio(r, 0);
        wg_fence();
        mma_kblock_mn2<true>(acc0, acc1, mkdesc(sb + A_V + slot * 2 * AT), mkdesc(sb + A_P + bslot * BT));
        wg_commit();
        wg_wait<0>();
        if (lane == 0) { mbar_arrive2(B.b_empty + 8 * bslot); mbar_arrive2(B.v_empty + 8 * slot); mbar_arrive2_remote(rv_empty + 8 * slot); }
        if (++slot == 3) slot = 0;
        if (++bslot == 3) bslot = 0;
      }
      for (int t = 1; t < 8; t++) {
        PH(3);
        mbar_wait(B.v_full + 8 * slot, (aph >> slot) & 1);
        aph ^= 1u << slot;
        PH(0);
        mbar_wait(B.p_full + 8 * bslot, (bph >> bslot) & 1);
        bph ^= 1u << bslot;
        PH(1);
        if (t <= 5) sprio(r, t);
        wg_fence();
        mma_kblock_mn2<false>(acc0, acc1, mkdesc(sb + A_V + slot * 2 * AT), mkdesc(sb + A_P + bslot * BT));
        wg_commit();
        wg_wait<0>();
        if (lane == 0) {
          mbar_arrive2(B.b_empty + 8 * bslot);
          if (r + 1 < nheads || t < 5) { mbar_arrive2(B.v_empty + 8 * slot); mbar_arrive2_remote(rv_empty + 8 * slot); }
        }
        PH(2);
        if (++slot == 3) slot = 0;
        if (++bslot == 3) bslot = 0;
      }
      PH(4);
      if (warp_in_wg == 0 && lane == 0) { CSTAMP(65 + r); TSTAMP(17 + r); }
      att_o_epilogue(p, sb, smem, hl, r, nheads, warp_in_wg, lane, acc0, acc1);
      if (warp_in_wg == 0 && lane == 0) CSTAMP(73 + r);
      PH(5);
    }
    PH_OUT(104);
  } else {
    const uint32_t full = sb + O_BAR, empty = full + 8 * O_NS, rempty = peer_addr(empty, rank ^ 1);
    int slot = 1, prev = 0;
    uint32_t ph = 0;
    mbar_wait(full, 0);
    wg_fence();
    mma_kblock_mn<true>(acc0, mkdesc(sb + 2 * AT), mkdesc(sb + 4 * AT));
    wg_commit();
    mma_kblock_mn<true>(acc1, mkdesc(sb + 3 * AT), mkdesc(sb + 4 * AT));
    wg_commit();
    for (int kb = 1; kb < 64; kb++) {
      mbar_wait(full + 8 * slot, ph);
      if (warp_in_wg == 0 && lane == 0 && kb >= 40 && kb < 48) DSTAMP(10 + kb - 40);
      const desc_t da = mkdesc(sb + slot * O_STG + 2 * AT), db = mkdesc(sb + slot * O_STG + 4 * AT);
      wg_fence();
      mma_kblock_mn<false>(acc0, da, db);
      wg_commit();
      wg_wait<1>();
      if (lane == 0 && kb - 1 + O_NS < 64) { mbar_arrive(empty + 8 * prev); mbar_arrive_remote(rempty + 8 * prev); }
      wg_fence();
      mma_kblock_mn<false>(acc1, da + (AT >> 4), db);
      wg_commit();
      prev = slot;
      if (++slot == O_NS) { slot = 0; ph ^= 1; }
    }
    wg_wait<0>();
    named_bar(2, 384);
    op_store_tile(p, sb, g, idx, 2, acc0, warp_in_wg, lane);
    op_store_tile(p, sb, g, idx, 3, acc1, warp_in_wg, lane);
    fence_async_smem();
    named_bar(5, 128);
    if (warp_in_wg == 0 && lane == 0) {
      op_issue_store(p, sb, g, idx, 2);
      op_issue_store(p, sb, g, idx, 3);
      bulk_commit();
      bulk_wait_read();
      TSTAMP(40);
    }
  }
}

__global__ void __launch_bounds__(NTHREADS, 1) fused_attn_kernel(const __grid_constant__ Params p) {
  extern __shared__ __align__(1024) uint8_t smem[];
  const uint32_t sb = smem_u32(smem);
  const int warp = __shfl_sync(0xffffffffu, threadIdx.x >> 5, 0), lane = threadIdx.x & 31;
  const int wg = warp >> 2, warp_in_wg = warp & 3;
  const int rank = blockIdx.x & 1;
  const int npair = gridDim.x >> 1, ps = npair >> 1;
  volatile int* s_slot = (volatile int*)(smem + SMEM_BYTES - 16);
  if (threadIdx.x == 32) {
    const AttBars B(sb + A_BAR);
    for (int i = 0; i < 6; i++) mbar_init(B.k_full + 8 * i, 1);
    for (int i = 0; i < 3; i++) {
      mbar_init(B.kw_full + 8 * i, 1); mbar_init(B.k_empty + 8 * i, 16);
      mbar_init(B.vw_full + 8 * i, 1); mbar_init(B.v_full + 8 * i, 1); mbar_init(B.v_empty + 8 * i, 16);
      mbar_init(B.x_full + 8 * i, 1); mbar_init(B.p_full + 8 * i, 4); mbar_init(B.b_empty + 8 * i, 8);
    }
    for (int i = 0; i < 2; i++) { mbar_init(B.xq_full + 8 * i, 1); mbar_init(B.xo_full + 8 * i, 1); }
    mbar_init(B.s_done, 8); mbar_init(B.xo_empty, 16); mbar_init(B.xq_empty, 8); mbar_init(B.xq_done, 8);
    mbar_init(B.q_ready, 8); mbar_init(B.l_ready, 8);
    mbar_init(B.o_full, 4); mbar_init(B.o_empty, 1);
    for (int i = 0; i < 8; i++) mbar_init(B.turn + 8 * i, 1);
    mbar_init(sb + A_BAR + 400, 1);
    *(volatile uint32_t*)(smem + A_BAR + 408) = 0;
    *(volatile uint32_t*)(smem + A_BAR + 412) = 0;
    asm volatile("fence.mbarrier_init.release.cluster;" ::: "memory");
  }
  if (threadIdx.x == 64) {
    for (int i = 0; i < 2; i++) {
      asm volatile("prefetch.tensormap [%0];" ::"l"(&p.tmK[i]) : "memory");
      asm volatile("prefetch.tensormap [%0];" ::"l"(&p.tmV[i]) : "memory");
      asm volatile("prefetch.tensormap [%0];" ::"l"(&p.tmWq[i]) : "memory");
      asm volatile("prefetch.tensormap [%0];" ::"l"(&p.tmX[i]) : "memory");
      asm volatile("prefetch.tensormap [%0];" ::"l"(&p.tmWo[i]) : "memory");
    }
  }
  if (threadIdx.x == 0 && rank == 0) {
    int slot = blockIdx.x >> 1;
    if (p.sidemap) {
      uint32_t v, t0, t1, best = 0xffffffffu;
      for (int i = 0; i < 2; i++) {
        asm volatile("mov.u32 %0, %clock;" : "=r"(t0)::"memory");
        asm volatile("atom.global.add.u32 %0, [%1], 0;" : "=r"(v) : "l"(&g_probe[0]) : "memory");
        asm volatile("{\n.reg .pred p;\nsetp.ne.u32 p, %1, 0x7fffffff;\nmov.u32 %0, 0;\n@p mov.u32 %0, %clock;\n}\n" : "=r"(t1) : "r"(v) : "memory");
        best = min(best, t1 - t0);
      }
      const int side = best > SIDE_THR ? 1 : 0;
      const int t = (int)atomicAdd(&g_ticket[side][0], 1);
      slot = t < ps ? side * ps + t : (side ^ 1) * ps + ps - 1 - (t - ps);
    }
    s_slot[0] = slot;
  }
  asm volatile("barrier.cluster.arrive.release.aligned;\nbarrier.cluster.wait.acquire.aligned;" ::: "memory");
  int pslot;
  asm volatile("ld.shared::cluster.s32 %0, [%1];" : "=r"(pslot) : "r"(peer_addr(sb + SMEM_BYTES - 16, 0)) : "memory");
  pslot = __shfl_sync(0xffffffffu, pslot, 0);
  if (p.sidemap && threadIdx.x == 32 && rank == 0) {
    if (atomicAdd(&g_done, 1) == (uint32_t)npair - 1) { g_ticket[0][0] = 0; g_ticket[1][0] = 0; g_done = 0; __threadfence(); }
  }
  const int blk = pslot >= ps ? 1 : 0, pr = pslot - blk * ps;
  const bool is_op = (pr & 3) == 3 && pr < 32;
  int g = 0, idx = 0, nheads;
  HeadList hl;
  hl.blk = blk;
  hl.stride = p.natt;
  hl.full = p.natt + 16;
  if (is_op) {
    const int m = pr >> 2;
    g = blk * 8 + 2 * (m >> 1) + rank;
    idx = m & 1;
    hl.i0 = NEARLY + 2 * m + rank;
    hl.i2 = 0;
    nheads = OPH;
  } else {
    const int i = 2 * (pr - min((pr + 1) >> 2, 8)) + rank;
    idx = i;
    hl.i0 = i < NEARLY ? i : i + 16;
    hl.i2 = OPH * hl.full + i;
    nheads = OPH + (8 * NH - hl.i2 + p.natt - 1) / p.natt;
  }
  if (threadIdx.x == 0) { TSTAMP(0); CSTAMP(64); }

  auto switch_role = [&](bool init) {
    named_bar(6, NTHREADS);
    if (init) {
      for (int i = 0; i < O_NS; i++) { mbar_init(sb + O_BAR + 8 * i, 1); mbar_init(sb + O_BAR + 8 * O_NS + 8 * i, 24); }
      *(volatile uint32_t*)(smem + O_BAR + 128) = 0;
      asm volatile("fence.mbarrier_init.release.cluster;" ::: "memory");
      const uint32_t sw = sb + A_BAR + 400;
      asm volatile("mbarrier.arrive.release.cluster.shared::cluster.b64 _, [%0];" ::"r"(peer_addr(sw, rank ^ 1)) : "memory");
      uint32_t ok, n = 0;
      do {
        asm volatile("{\n.reg .pred p;\nmbarrier.try_wait.parity.acquire.cluster.shared::cta.b64 p, [%1], 0;\nselp.u32 %0, 1, 0, p;\n}\n"
                     : "=r"(ok) : "r"(sw) : "memory");
        if (++n > WAIT_LIMIT) __trap();
      } while (!ok);
    }
    named_bar(7, NTHREADS);
  };
  const bool run_att = p.mode != 3, run_op = is_op && p.mode != 2;

  if (wg == 0) {
    asm volatile("setmaxnreg.dec.sync.aligned.u32 32;");
    if (run_att) att_producer(p, sb, hl, rank, nheads, warp, lane);
    if (run_op) {
      __syncwarp();
      switch_role(threadIdx.x == 0);
      op_producer(p, sb, smem, g, idx, rank, warp, lane);
    }
  } else if (wg == 3) {
    asm volatile("setmaxnreg.inc.sync.aligned.u32 176;");
    float acc0[72], acc1[72];
    const int ph0 = run_att ? 0 : 1, ph1 = run_op ? 2 : 1;
#pragma unroll 1
    for (int phase = ph0; phase < ph1; phase++) {
      if (phase == 1) switch_role(false);
      wg3_role(p, sb, smem, phase == 0, g, idx, rank, hl, nheads, warp_in_wg, lane, acc0, acc1);
    }
  } else {
    asm volatile("setmaxnreg.inc.sync.aligned.u32 152;");
    if (run_att) {
      if (!is_op) { const long long t0 = clock64(); const long long d = STAG_EXPR; while (clock64() - t0 < d) __nanosleep(100); }
      att_s_role(sb, smem, wg - 1, rank, nheads, warp_in_wg, lane);
    }
    if (run_op) {
      switch_role(false);
      op_consumer1(p, sb, g, idx, rank, wg - 1, warp_in_wg, lane);
    }
  }
}

typedef CUresult (*EncodeFn)(CUtensorMap*, CUtensorMapDataType, cuuint32_t, void*, const cuuint64_t*, const cuuint64_t*,
                             const cuuint32_t*, const cuuint32_t*, CUtensorMapInterleave, CUtensorMapSwizzle,
                             CUtensorMapL2promotion, CUtensorMapFloatOOBfill);

void make_map(EncodeFn enc, CUtensorMap* m, const void* ptr, int rank, const cuuint64_t* dims, const cuuint64_t* strides,
              const cuuint32_t* box) {
  const cuuint32_t es[3] = {1, 1, 1};
  CUresult r = enc(m, CU_TENSOR_MAP_DATA_TYPE_BFLOAT16, rank, const_cast<void*>(ptr), dims, strides, box, es,
                   CU_TENSOR_MAP_INTERLEAVE_NONE, CU_TENSOR_MAP_SWIZZLE_128B, L2PROMO,
                   CU_TENSOR_MAP_FLOAT_OOB_FILL_NONE);
  (void)r;
}

}

#define KERNEL_MODE_SEQ 0

extern "C" void kernel_launch(void* const* d_in, const int* in_sizes, int n_in, void* d_out, int out_size) {
  (void)in_sizes; (void)n_in; (void)out_size;
  void* fn = nullptr;
  cudaDriverEntryPointQueryResult qr;
  cudaGetDriverEntryPoint("cuTensorMapEncodeTiled", &fn, cudaEnableDefault, &qr);
  EncodeFn enc = (EncodeFn)fn;
  Params p;
  for (int blk = 0; blk < 2; blk++) {
    const void* x = d_in[blk * 5 + 0];
    const void* k = d_in[blk * 5 + 1];
    const void* v = d_in[blk * 5 + 2];
    const void* wq = d_in[blk * 5 + 3];
    const void* wo = d_in[blk * 5 + 4];
    {
      const cuuint64_t dims[3] = {64, (cuuint64_t)NBATCH * NH * SK, 2}, str[2] = {256, 128};
      const cuuint32_t box[3] = {64, 64, 2};
      make_map(enc, &p.tmK[blk], k, 3, dims, str, box);
      make_map(enc, &p.tmV[blk], v, 3, dims, str, box);
    }
    {
      const cuuint64_t dims[3] = {64, DM, (cuuint64_t)NH * 2}, str[2] = {NH * DH * 2, 128};
      const cuuint32_t box[3] = {64, 64, 1};
      make_map(enc, &p.tmWq[blk], wq, 3, dims, str, box);
    }
    {
      const cuuint64_t dims[3] = {64, (cuuint64_t)NH * DH, 8}, str[2] = {DM * 2, 128};
      const cuuint32_t box[3] = {64, 64, 2};
      make_map(enc, &p.tmWo[blk], wo, 3, dims, str, box);
    }
    {
      const cuuint64_t dims[2] = {DM, (cuuint64_t)NBATCH * SQ}, str[1] = {DM * 2};
      const cuuint32_t box[2] = {64, SQ};
      make_map(enc, &p.tmX[blk], x, 2, dims, str, box);
    }
    p.K[blk] = (const __nv_bfloat16*)k;
    p.V[blk] = (const __nv_bfloat16*)v;
    p.X[blk] = (const __nv_bfloat16*)x;
    p.Wq[blk] = (const __nv_bfloat16*)wq;
    p.Wo[blk] = (const __nv_bfloat16*)wo;
  }
  {
    const cuuint64_t dims[2] = {2 * DM, (cuuint64_t)NBATCH * SQ}, str[1] = {2 * DM * 2};
    const cuuint32_t box[2] = {64, SQ};
    make_map(enc, &p.tmOut, d_out, 2, dims, str, box);
  }
  cudaFuncSetAttribute(fused_attn_kernel, cudaFuncAttributeMaxDynamicSharedMemorySize, SMEM_BYTES);
  int nsm = 132;
  cudaDeviceGetAttribute(&nsm, cudaDevAttrMultiProcessorCount, 0);
  if (nsm > 132) nsm = 132;
  nsm &= ~3;
  p.natt = nsm / 2 - 16;
  p.sidemap = 1;
  cudaLaunchConfig_t cfg = {};
  cfg.gridDim = dim3(nsm);
  cfg.blockDim = dim3(NTHREADS);
  cfg.dynamicSmemBytes = SMEM_BYTES;
  cfg.stream = cudaStreamPerThread;
  cudaLaunchAttribute at[1];
  at[0].id = cudaLaunchAttributeClusterDimension;
  at[0].val.clusterDim.x = 2;
  at[0].val.clusterDim.y = 1;
  at[0].val.clusterDim.z = 1;
  cfg.attrs = at;
  cfg.numAttrs = 1;
  p.mode = 0;
  cudaLaunchKernelEx(&cfg, fused_attn_kernel, p);
}
```

```cpp
#include <cuda_runtime.h>
#include <cuda_bf16.h>
#include <cuda.h>
#include <stdint.h>
#define DBG_SYNC(tag)

namespace {

constexpr int NBATCH = 8, SQ = 144, DM = 512, NH = 32, DH = 128, SK = 512;
constexpr int NGRP = 16;
constexpr int BT = SQ * 128;
constexpr int AT = 64 * 128;
constexpr int QIMG = 2 * BT;
constexpr int NTHREADS = 512;
constexpr int SMEM_BYTES = 232448;
constexpr uint32_t WAIT_LIMIT = 1u << 20;
#define PUB_FIRST
#define PLAIN_EX2
#define L2PROMO CU_TENSOR_MAP_L2_PROMOTION_NONE
#define SIDE_THR 430
#define STAG_EXPR (idx < 40 ? (long long)(idx >> 1) * STAG_STEP : (long long)STAG_LAST)
#define STAG_STEP 600
#define STAG_LAST 14000
#define OPH 1
#define OSPLIT 9
#define SPRIO 60
#define KV_PFK 0
#define KV_PF0 1
#define KV_PFV 0
#define KV0_PF 0
#define KV0_DELAY 1500
#define DBGR 2
#define NEARLY 0
#define NWK 5
#define CLUSTER 2
#define W_PF 0
#define TURN_AT 16
#define PF_DIST 0

constexpr int A_Q = 0;
constexpr int A_O = A_Q + QIMG;
constexpr int A_P = A_O + QIMG;
constexpr int A_K = A_P + 3 * BT;
constexpr int A_V = A_K + 3 * 2 * AT;
constexpr int A_L = A_V + 3 * 2 * AT;
constexpr int A_FB = A_L + SQ * 4;
constexpr int A_BAR = A_L + 8 * SQ * 4;
static_assert(A_BAR % 8 == 0 && A_BAR + 464 <= SMEM_BYTES - 16 && A_FB + 648 * 4 <= A_BAR, "att smem");
constexpr int O_NS = 4;
constexpr int O_STG = 4 * AT + BT;
constexpr int O_BAR = O_NS * O_STG;
static_assert(O_STG % 1024 == 0 && O_BAR + 256 <= SMEM_BYTES, "op smem");

struct alignas(64) Params {
  CUtensorMap tmK[2], tmV[2], tmWq[2], tmWo[2], tmX[2], tmOut;
  const __nv_bfloat16* K[2];
  const __nv_bfloat16* V[2];
  const __nv_bfloat16* X[2];
  const __nv_bfloat16* Wq[2];
  const __nv_bfloat16* Wo[2];
  int natt;
  int mode;
};

__device__ uint8_t g_O[NGRP * NH * QIMG];
__device__ uint32_t g_oflag[2][NGRP * NH];

#define TSTAMP(i)
#define CSTAMP(i)
#define DSTAMP(i)
#define PH_DECL
#define PH(i)
#define PH_OUT(base)
#define EP(i)
__device__ __forceinline__ uint32_t smem_u32(const void* p) { return (uint32_t)__cvta_generic_to_shared(p); }
__device__ __forceinline__ void mbar_init(uint32_t bar, uint32_t cnt) {
  asm volatile("mbarrier.init.shared::cta.b64 [%0], %1;" ::"r"(bar), "r"(cnt) : "memory");
}
__device__ __forceinline__ void mbar_expect_tx(uint32_t bar, uint32_t bytes) {
  asm volatile("mbarrier.arrive.expect_tx.shared::cta.b64 _, [%0], %1;" ::"r"(bar), "r"(bytes) : "memory");
}
__device__ __forceinline__ void mbar_arrive(uint32_t bar) {
  asm volatile("mbarrier.arrive.shared::cta.b64 _, [%0];" ::"r"(bar) : "memory");
}
__device__ __forceinline__ void mbar_arrive2(uint32_t bar) {
  asm volatile("mbarrier.arrive.shared::cta.b64 _, [%0], 2;" ::"r"(bar) : "memory");
}
__device__ __forceinline__ uint32_t peer_addr(uint32_t addr, uint32_t peer) {
  uint32_t r;
  asm volatile("mapa.shared::cluster.u32 %0, %1, %2;" : "=r"(r) : "r"(addr), "r"(peer));
  return r;
}
__device__ __forceinline__ void mbar_arrive_remote(uint32_t rbar) {
  asm volatile("mbarrier.arrive.shared::cluster.b64 _, [%0];" ::"r"(rbar) : "memory");
}
__device__ __forceinline__ void mbar_arrive2_remote(uint32_t rbar) {
  asm volatile("mbarrier.arrive.shared::cluster.b64 _, [%0], 2;" ::"r"(rbar) : "memory");
}
__device__ __forceinline__ bool mbar_try(uint32_t bar, uint32_t parity) {
  uint32_t ok;
  asm volatile(
      "{\n.reg .pred p;\nmbarrier.try_wait.parity.shared::cta.b64 p, [%1], %2;\nselp.u32 %0, 1, 0, p;\n}\n"
      : "=r"(ok)
      : "r"(bar), "r"(parity)
      : "memory");
  return ok;
}
__device__ __forceinline__ void mbar_wait(uint32_t bar, uint32_t parity) {
  if (mbar_try(bar, parity)) return;
  uint32_t n = 0;
  while (!mbar_try(bar, parity)) {
    if (++n > WAIT_LIMIT) __trap();
  }
}
__device__ __forceinline__ void fence_async_smem() { asm volatile("fence.proxy.async.shared::cta;" ::: "memory"); }
__device__ __forceinline__ void fence_async_all() { asm volatile("fence.proxy.async;" ::: "memory"); }
__device__ __forceinline__ void named_bar(int id, int n) { asm volatile("bar.sync %0, %1;" ::"r"(id), "r"(n) : "memory"); }

__device__ __forceinline__ uint64_t policy_evict_first() {
  uint64_t p;
  asm volatile("createpolicy.fractional.L2::evict_first.b64 %0, 1.0;" : "=l"(p));
  return p;
}
__device__ __forceinline__ void tma2d(uint32_t dst, const CUtensorMap* tm, int c0, int c1, uint32_t bar) {
  asm volatile("cp.async.bulk.tensor.2d.shared::cluster.global.mbarrier::complete_tx::bytes [%0], [%1, {%3, %4}], [%2];" ::"r"(dst),
               "l"(tm), "r"(bar), "r"(c0), "r"(c1)
               : "memory");
}
__device__ __forceinline__ void tma3d(uint32_t dst, const CUtensorMap* tm, int c0, int c1, int c2, uint32_t bar) {
  asm volatile("cp.async.bulk.tensor.3d.shared::cluster.global.mbarrier::complete_tx::bytes [%0], [%1, {%3, %4, %5}], [%2];" ::"r"(dst),
               "l"(tm), "r"(bar), "r"(c0), "r"(c1), "r"(c2)
               : "memory");
}
__device__ __forceinline__ void tma3d_mc(uint32_t dst, const CUtensorMap* tm, int c0, int c1, int c2, uint32_t bar) {
  asm volatile(
      "cp.async.bulk.tensor.3d.shared::cluster.global.mbarrier::complete_tx::bytes.multicast::cluster [%0], [%1, {%3, %4, %5}], [%2], %6;" ::"r"(dst),
      "l"(tm), "r"(bar), "r"(c0), "r"(c1), "r"(c2), "h"((uint16_t)3)
      : "memory");
}
__device__ __forceinline__ void tma3d_hint(uint32_t dst, const CUtensorMap* tm, int c0, int c1, int c2, uint32_t bar, uint64_t pol) {
  asm volatile(
      "cp.async.bulk.tensor.3d.shared::cluster.global.mbarrier::complete_tx::bytes.L2::cache_hint [%0], [%1, {%3, %4, %5}], [%2], %6;" ::"r"(dst),
      "l"(tm), "r"(bar), "r"(c0), "r"(c1), "r"(c2), "l"(pol)
      : "memory");
}
__device__ __forceinline__ void tma2d_prefetch(const CUtensorMap* tm, int c0, int c1) {
  asm volatile("cp.async.bulk.prefetch.tensor.2d.L2.global [%0, {%1, %2}];" ::"l"(tm), "r"(c0), "r"(c1) : "memory");
}
__device__ __forceinline__ void tma3d_prefetch(const CUtensorMap* tm, int c0, int c1, int c2) {
  asm volatile("cp.async.bulk.prefetch.tensor.3d.L2.global [%0, {%1, %2, %3}];" ::"l"(tm), "r"(c0), "r"(c1), "r"(c2) : "memory");
}
__device__ __forceinline__ void bulk_load(uint32_t dst, const void* src, uint32_t bytes, uint32_t bar) {
  asm volatile("cp.async.bulk.shared::cluster.global.mbarrier::complete_tx::bytes [%0], [%1], %2, [%3];" ::"r"(dst), "l"(src),
               "r"(bytes), "r"(bar)
               : "memory");
}
__device__ __forceinline__ void bulk_store(void* dst, uint32_t src, uint32_t bytes) {
  asm volatile("cp.async.bulk.global.shared::cta.bulk_group [%0], [%1], %2;" ::"l"(dst), "r"(src), "r"(bytes) : "memory");
}
__device__ __forceinline__ void tma2d_store(const CUtensorMap* tm, uint32_t src, int c0, int c1) {
  asm volatile("cp.async.bulk.tensor.2d.global.shared::cta.bulk_group [%0, {%2, %3}], [%1];" ::"l"(tm), "r"(src), "r"(c0), "r"(c1)
               : "memory");
}
__device__ __forceinline__ void bulk_commit() { asm volatile("cp.async.bulk.commit_group;" ::: "memory"); }
__device__ __forceinline__ void bulk_wait_read() { asm volatile("cp.async.bulk.wait_group.read 0;" ::: "memory"); }
__device__ __forceinline__ void bulk_wait_all() { asm volatile("cp.async.bulk.wait_group 0;" ::: "memory"); }
__device__ __forceinline__ void l2_prefetch(const void* src, uint32_t bytes, uint64_t pol) {
  asm volatile("cp.async.bulk.prefetch.L2.global.L2::cache_hint [%0], %1, %2;" ::"l"(src), "r"(bytes), "l"(pol) : "memory");
}
__device__ __forceinline__ void tlb_warm(const void* a) {
  asm volatile("cp.async.bulk.prefetch.L2.global [%0], 128;" ::"l"(a) : "memory");
}
__device__ __forceinline__ void lsu_prefetch(const void* a) { asm volatile("prefetch.global.L2 [%0];" ::"l"(a)); }
__device__ __forceinline__ void flag_add_release(uint32_t* f) {
  asm volatile("red.release.gpu.global.add.u32 [%0], 1;" ::"l"(f) : "memory");
}
__device__ __forceinline__ void flag_wait_reset(uint32_t* f, uint32_t target) {
  uint32_t v, n = 0;
  while (true) {
    asm volatile("ld.acquire.gpu.global.u32 %0, [%1];" : "=r"(v) : "l"(f) : "memory");
    if (v >= target) break;
    if (++n > (1u << 24)) __trap();
    __nanosleep(20);
  }
  asm volatile("st.relaxed.gpu.global.u32 [%0], %1;" ::"l"(f), "r"(0u) : "memory");
  fence_async_all();
}

__device__ __forceinline__ void wg_fence() { asm volatile("wgmma.fence.sync.aligned;" ::: "memory"); }
__device__ __forceinline__ void wg_commit() { asm volatile("wgmma.commit_group.sync.aligned;" ::: "memory"); }
template <int N>
__device__ __forceinline__ void wg_wait() {
  asm volatile("wgmma.wait_group.sync.aligned %0;" ::"n"(N) : "memory");
}
typedef uint32_t desc_t;
__device__ __forceinline__ desc_t mkdesc(uint32_t addr) { return ((addr & 0x3FFFF) >> 4) | (1u << 16); }

#define ACC8(c, o) c(d[o]), c(d[o + 1]), c(d[o + 2]), c(d[o + 3]), c(d[o + 4]), c(d[o + 5]), c(d[o + 6]), c(d[o + 7])
#define ACC72(c) ACC8(c, 0), ACC8(c, 8), ACC8(c, 16), ACC8(c, 24), ACC8(c, 32), ACC8(c, 40), ACC8(c, 48), ACC8(c, 56), ACC8(c, 64)
#define WGMMA144_HEAD                                                                                                          \
  "wgmma.mma_async.sync.aligned.m64n144k16.f32.bf16.bf16 "                                                                     \
  "{%0, %1, %2, %3, %4, %5, %6, %7, %8, %9, %10, %11, %12, %13, %14, %15, %16, %17, %18, %19, %20, %21, %22, %23, "            \
  "%24, %25, %26, %27, %28, %29, %30, %31, %32, %33, %34, %35, %36, %37, %38, %39, %40, %41, %42, %43, %44, %45, %46, %47, "   \
  "%48, %49, %50, %51, %52, %53, %54, %55, %56, %57, %58, %59, %60, %61, %62, %63, %64, %65, %66, %67, %68, %69, %70, %71}, "
template <int TA, bool INIT>
__device__ __forceinline__ void wgmma144(float (&d)[72], desc_t da, desc_t db) {
  if constexpr (INIT) {
    asm volatile("{\n.reg .pred p;\n.reg .b64 da, db;\n.reg .b32 hi;\nmov.b32 hi, 0x40000040;\nmov.b64 da, {%72, hi};\n"
                 "mov.b64 db, {%73, hi};\nsetp.ne.b32 p, 0, 0;\n" WGMMA144_HEAD "da, db, p, 1, 1, %74, 0;\n}\n"
                 : ACC72("=f")
                 : "r"(da), "r"(db), "n"(TA));
  } else {
    asm volatile("{\n.reg .pred p;\n.reg .b64 da, db;\n.reg .b32 hi;\nmov.b32 hi, 0x40000040;\nmov.b64 da, {%72, hi};\n"
                 "mov.b64 db, {%73, hi};\nsetp.eq.b32 p, 0, 0;\n" WGMMA144_HEAD "da, db, p, 1, 1, %74, 0;\n}\n"
                 : ACC72("+f")
                 : "r"(da), "r"(db), "n"(TA));
  }
}
template <bool INIT>
__device__ __forceinline__ void mma_kblock_mn(float (&d)[72], desc_t da, desc_t db) {
  wgmma144<1, INIT>(d, da, db);
  wgmma144<1, false>(d, da + 128, db + 2);
  wgmma144<1, false>(d, da + 256, db + 4);
  wgmma144<1, false>(d, da + 384, db + 6);
}
template <bool INIT>
__device__ __forceinline__ void mma_kblock_mn2(float (&d0)[72], float (&d1)[72], desc_t da, desc_t db) {
  wgmma144<1, INIT>(d0, da, db);
  wgmma144<1, INIT>(d1, da + (AT >> 4), db);
#pragma unroll
  for (int kk = 1; kk < 4; kk++) {
    wgmma144<1, false>(d0, da + kk * 128, db + kk * 2);
    wgmma144<1, false>(d1, da + kk * 128 + (AT >> 4), db + kk * 2);
  }
}
__device__ __forceinline__ uint32_t pack_bf16(float lo, float hi) {
  uint32_t r;
  asm("cvt.rn.bf16x2.f32 %0, %1, %2;" : "=r"(r) : "f"(hi), "f"(lo));
  return r;
}
__device__ __forceinline__ void stsm_t4(uint32_t addr, uint32_t r0, uint32_t r1, uint32_t r2, uint32_t r3) {
  asm volatile("stmatrix.sync.aligned.m8n8.x4.trans.shared.b16 [%0], {%1, %2, %3, %4};" ::"r"(addr), "r"(r0), "r"(r1), "r"(r2),
               "r"(r3)
               : "memory");
}
__device__ __forceinline__ float ex2(float x) {
  float y;
  asm volatile("ex2.approx.ftz.f32 %0, %1;" : "=f"(y) : "f"(x));
  return y;
}
__device__ __forceinline__ void ex2x8_dep(float* x, uint32_t dep) {
  asm volatile(
      "{\n.reg .pred p;\nsetp.ne.u32 p, %8, 0xFFFFFFFF;\n"
      "@p ex2.approx.ftz.f32 %0, %0;\n@p ex2.approx.ftz.f32 %1, %1;\n@p ex2.approx.ftz.f32 %2, %2;\n@p ex2.approx.ftz.f32 %3, %3;\n"
      "@p ex2.approx.ftz.f32 %4, %4;\n@p ex2.approx.ftz.f32 %5, %5;\n@p ex2.approx.ftz.f32 %6, %6;\n@p ex2.approx.ftz.f32 %7, %7;\n}\n"
      : "+f"(x[0]), "+f"(x[1]), "+f"(x[2]), "+f"(x[3]), "+f"(x[4]), "+f"(x[5]), "+f"(x[6]), "+f"(x[7])
      : "r"(dep));
}
__device__ __forceinline__ uint32_t stsm_lane_off(int warp_in_wg, int lane) {
  int mi = lane >> 3, rr = lane & 7;
  return (uint32_t)(((mi >> 1) * 8 + rr) * 128 + (((2 * warp_in_wg + (mi & 1)) ^ rr) << 4));
}
__device__ __forceinline__ void store_tile_scaled(const float (&d)[72], uint32_t base, float s) {
#pragma unroll
  for (int j = 0; j < 18; j += 2) {
    stsm_t4(base + j * 1024, pack_bf16(d[4 * j] * s, d[4 * j + 1] * s), pack_bf16(d[4 * j + 2] * s, d[4 * j + 3] * s),
            pack_bf16(d[4 * j + 4] * s, d[4 * j + 5] * s), pack_bf16(d[4 * j + 6] * s, d[4 * j + 7] * s));
  }
}

struct AttBars {
  uint32_t kw_full, k_full, k_empty, vw_full, v_full, v_empty, x_full, p_full, b_empty, xq_full, xo_full, s_done, xo_empty, q_ready,
      l_ready, li_ready, o_full, o_empty, turn, xq_empty, xq_done, k_free, v_free;
  __device__ __forceinline__ AttBars(uint32_t b)
      : kw_full(b), k_full(b + 24), k_empty(b + 72), vw_full(b + 96), v_full(b + 120), v_empty(b + 144), x_full(b + 168),
        p_full(b + 192), b_empty(b + 216), xq_full(b + 240), xo_full(b + 256), s_done(b + 272), xo_empty(b + 280),
        q_ready(b + 288), l_ready(b + 296), li_ready(b + 304), o_full(b + 312), o_empty(b + 320), turn(b + 328), xq_empty(b + 304), xq_done(b + 392), k_free(b + 416), v_free(b + 440) {}
};
constexpr int ATT_BAR_BYTES = 400;
struct HeadList { int blk, i0, i2, full, stride; };
struct HeadId { int g, h; };
__device__ __forceinline__ HeadId att_head(const HeadList& hl, int r) {
  const int hi = r < OPH ? hl.i0 + r * hl.full : hl.i2 + (r - OPH) * hl.stride;
  return {hl.blk * 8 + (hi & 7), hi >> 3};
}
#define KVROW(id) ((((id).g & 7) * NH + (id).h) * SK)

__device__ __forceinline__ void att_producer(const Params& p, uint32_t sb, const HeadList& hl, int rank, int nheads, int warp,
                                             int lane) {
  const AttBars B(sb + A_BAR);
  if (lane != 0 && warp != 3) return;
  if (warp == 0 || warp == 1) {
    const bool isk = warp == 0;
    const int nw = isk ? 5 : 3;
    const uint32_t wlist = isk ? 0x65210u : 0x743u;
    const uint32_t base = sb + (isk ? A_K : A_V), empty = isk ? B.k_empty : B.v_empty, wfull = isk ? B.kw_full : B.vw_full;
    const uint64_t pol = policy_evict_first();
    int slot = 0, n6 = 0;
    const uint32_t lfree = isk ? B.k_free : B.v_free;
    uint32_t eph = 0, fph = 0;
    int used = 0;
    for (int r = 0; r < nheads; r++) {
      const HeadId id = att_head(hl, r);
      const int blk = id.g >> 3;
      for (int j = 0; j < nw + 8; j++) {
        const uint32_t dst = base + slot * 2 * AT;
        if (used >= 3) {
          if (j < nw) { mbar_wait(empty + 8 * slot, (eph >> slot) & 1); eph ^= 1u << slot; }
          else { mbar_wait(lfree + 8 * slot, (fph >> slot) & 1); fph ^= 1u << slot; }
        }
        used++;
        if (r == 0 && j < 3) {
          if (isk) { if (j > 0) mbar_wait(B.kw_full + 8 * (j - 1), 0); }
          else mbar_wait(B.kw_full + 8 * (j == 0 ? 0 : (j == 1 ? 1 : 2)), 0);
        }
        if (j < nw) {
          const int wj = (wlist >> (4 * j)) & 15;
          if (r == DBGR) DSTAMP(20 + wj);
          mbar_expect_tx(wfull + 8 * slot, 2 * AT);
          tma3d_mc(dst + rank * AT, &p.tmWq[blk], 0, wj * 64, id.h * 2 + rank, wfull + 8 * slot);
        } else {
          const uint32_t full = isk ? B.k_full + 8 * n6 : B.v_full + 8 * slot;
          mbar_expect_tx(full, 2 * AT);
          tma3d_hint(dst, isk ? &p.tmK[blk] : &p.tmV[blk], 0, KVROW(id) + (j - nw) * 64, 0, full, pol);
          if (++n6 == 6) n6 = 0;
        }
        if (++slot == 3) slot = 0;
      }
    }
  } else if (warp == 2) {
    int slot = 0;
    uint32_t ph = 1;
    for (int r = 0; r < nheads; r++) {
      const HeadId id = att_head(hl, r);
      const CUtensorMap* tm = &p.tmX[id.g >> 3];
      const int row = (id.g & 7) * SQ;
      auto load_x = [&](int j, uint32_t dst, uint32_t bar) {
        if (r == DBGR) DSTAMP(30 + j);
        mbar_expect_tx(bar, BT);
        tma2d(dst, tm, j * 64, row, bar);
      };
      auto load_b = [&](int j) {
        mbar_wait(B.b_empty + 8 * slot, ph);
        load_x(j, sb + A_P + slot * BT, B.x_full + 8 * slot);
        if (++slot == 3) { slot = 0; ph ^= 1; }
      };
      if (r == 0) {
        load_x(0, sb + A_O, B.xo_full);
        load_x(1, sb + A_O + BT, B.xo_full + 8);
        mbar_wait(B.xo_full, 0);
      } else {
        mbar_wait(B.s_done, (r - 1) & 1);
      }
      load_x(2, sb + A_Q, B.xq_full);
      if (r == 0) mbar_wait(B.xo_full + 8, 0);
      load_x(3, sb + A_Q + BT, B.xq_full + 8);
      if (r == 0) mbar_wait(B.xq_full, 0);
      load_b(4);
      if (r == 0) mbar_wait(B.xq_full + 8, 0);
      load_b(5);
      mbar_wait(B.xq_empty, (r & 1));
      load_x(6, sb + A_Q, B.xq_full);
      load_b(7);
      mbar_wait(B.b_empty + 8 * slot, ph);
      if (++slot == 3) { slot = 0; ph ^= 1; }
      for (int t = 0; t < 8; t++) {
        mbar_wait(B.b_empty + 8 * slot, ph);
        if (++slot == 3) { slot = 0; ph ^= 1; }
      }
    }
  } else {
    auto prefetch_w = [&](int r) {
      const HeadId id = att_head(hl, r);
      const uint8_t* src = (const uint8_t*)((id.g >> 3) ? p.Wq[1] : p.Wq[0]) + (id.h * DH + rank * 64) * 2 + (size_t)lane * (NH * DH * 2);
#pragma unroll 4
      for (int k = 0; k < 16; k++) lsu_prefetch(src + (size_t)k * 32 * (NH * DH * 2));
    };
    auto load_x01 = [&](int r) {
      const HeadId nx = att_head(hl, r);
      for (int j = 0; j < 2; j++) {
        if (r == DBGR) DSTAMP(30 + j);
        mbar_expect_tx(B.xo_full + 8 * j, BT);
        tma2d(sb + A_O + j * BT, &p.tmX[nx.g >> 3], j * 64, (nx.g & 7) * SQ, B.xo_full + 8 * j);
      }
    };
    if (W_PF == 1 && nheads > 1) prefetch_w(1);
    if (lane == 0 && nheads > 1) {
      mbar_wait(B.xo_empty, 0);
      load_x01(1);
    }
    auto prefetch_kv = [&](int r) {
      const HeadId id = att_head(hl, r);
      const size_t off = (size_t)KVROW(id) * (DH * 2) + lane * 128;
      const uint8_t* k = (const uint8_t*)((id.g >> 3) ? p.K[1] : p.K[0]) + off;
      const uint8_t* v = (const uint8_t*)((id.g >> 3) ? p.V[1] : p.V[0]) + off;
#pragma unroll 4
      for (int i = 4 * KV_PF0; i < 4 * KV_PFK; i++) lsu_prefetch(k + i * 4096);
#pragma unroll 4
      for (int i = 0; i < 4 * KV_PFV; i++) lsu_prefetch(v + i * 4096);
    };
    for (int r = 0; r < nheads; r++) {
      if (KV_PFK > 0 && r + 1 < nheads) {
        if (lane == 0) mbar_wait(B.s_done, r & 1);
        __syncwarp();
        prefetch_kv(r + 1);
      }
      if (lane == 0) {
        const HeadId id = att_head(hl, r);
        const int hh = id.g * NH + id.h;
        mbar_wait(B.o_full, r & 1);
        if (r < 2) DSTAMP(40 + 0 + 4 * r + 2);
#pragma unroll
        for (int c = 0; c < OSPLIT; c++) bulk_store(g_O + (size_t)hh * QIMG + c * (QIMG / OSPLIT), sb + A_O + c * (QIMG / OSPLIT), QIMG / OSPLIT);
        bulk_commit();
        bulk_wait_read();
        if (r < 2) DSTAMP(40 + 1 + 4 * r + 2);
        mbar_arrive(B.o_empty);
        if (r + 2 < nheads) load_x01(r + 2);
        bulk_wait_all();
        if (r < 2) DSTAMP(40 + 2 + 4 * r + 2);
        asm volatile("red.relaxed.gpu.global.add.u32 [%0], 1;" ::"l"(&g_oflag[0][hh]) : "memory");
        asm volatile("red.relaxed.gpu.global.add.u32 [%0], 1;" ::"l"(&g_oflag[1][hh]) : "memory");
        if (r < 2) DSTAMP(40 + 3 + 4 * r + 2);
        TSTAMP(9 + r);
      }
      __syncwarp();
      if (W_PF == 1 && r + 2 < nheads) prefetch_w(r + 2);
    }
  }
}

__device__ __forceinline__ void att_s_role(uint32_t sb, uint8_t* smem, int w, int rank, int nheads, int warp_in_wg, int lane) {
  const AttBars B(sb + A_BAR);
  const uint32_t rk_empty = peer_addr(B.k_empty, rank ^ 1);
  const uint32_t st_off = stsm_lane_off(warp_in_wg, lane);
  const float qscale = 0.08838834764831845f * 1.4426950408889634f;
  float acc[72], l[36];
#pragma unroll
  for (int i = 0; i < 36; i++) l[i] = 0.f;
  const uint32_t my_turn = B.turn + 8 * (w * 4 + warp_in_wg), other_turn = B.turn + 8 * ((w ^ 1) * 4 + warp_in_wg);
  uint32_t tph = w ^ 1;
  uint32_t kwph = 0, vwph = 0;
  int kuse = 0, vuse = 0;
  int n6 = w;
  uint32_t nph = 0;
  auto flush_l = [&]() {
      float v[18], u[10];
      const bool b4 = lane & 16, b3 = lane & 8, b2 = lane & 4;
#pragma unroll
      for (int i = 0; i < 18; i++) {
        const float keep = b4 ? l[i + 18] : l[i], send = b4 ? l[i] : l[i + 18];
        v[i] = keep + __shfl_xor_sync(0xffffffffu, send, 16);
      }
#pragma unroll
      for (int i = 0; i < 9; i++) {
        const float keep = b3 ? v[i + 9] : v[i], send = b3 ? v[i] : v[i + 9];
        u[i] = keep + __shfl_xor_sync(0xffffffffu, send, 8);
      }
      u[9] = 0.f;
      float* lp = (float*)(smem + A_L) + (w * 4 + warp_in_wg) * SQ + 2 * (lane & 3);
      const int ibase = (b4 ? 18 : 0) + (b3 ? 9 : 0) + (b2 ? 5 : 0);
#pragma unroll
      for (int i = 0; i < 5; i++) {
        const float keep = b2 ? u[i + 5] : u[i], send = b2 ? u[i] : u[i + 5];
        const float sum = keep + __shfl_xor_sync(0xffffffffu, send, 4);
        const int idx = ibase + i;
        if (!(b2 && i == 4)) lp[8 * (idx >> 1) + (idx & 1)] = sum;
      }
      __syncwarp();
      if (lane == 0) mbar_arrive(B.l_ready);
#pragma unroll
      for (int i = 0; i < 36; i++) l[i] = 0.f;
  };
  PH_DECL;
  for (int r = 0; r < nheads; r++) {
#define SSTAMP(k) do { if (w == 0 && warp_in_wg == 0 && lane == 0 && r < 6) CSTAMP(96 + 4 * r + (k)); } while (0)
    SSTAMP(0);
    {
      auto step = [&](int j, uint32_t& xa, uint32_t& wa, uint32_t& rel_x, uint32_t& rel_w, uint32_t& rel_wr) {
        if (j < 2) {
          mbar_wait(B.xo_full + 8 * j, r & 1);
          xa = sb + A_O + j * BT;
          rel_x = B.xo_empty;
        } else if (j < 4 || j == 6) {
          const int h = j == 3 ? 1 : 0;
          mbar_wait(B.xq_full + 8 * h, h ? (r & 1) : (j == 6 ? 1 : 0));
          xa = sb + A_Q + h * BT;
          rel_x = j == 2 ? B.xq_empty : (j == 6 ? B.xq_done : 0);
        } else {
          const int sl = j == 7 ? 2 : j - 4;
          mbar_wait(B.x_full + 8 * sl, r & 1);
          xa = sb + A_P + sl * BT;
          rel_x = B.b_empty + 8 * sl;
        }
        if (j < 3 || j == 5 || j == 6) {
          const int sl = (kuse + (j < 3 ? j : j - 2)) % 3;
          mbar_wait(B.kw_full + 8 * sl, (kwph >> sl) & 1);
          kwph ^= 1u << sl;
          wa = sb + A_K + sl * 2 * AT + w * AT;
          if (j < 2) { rel_w = B.k_empty + 8 * sl; rel_wr = rk_empty + 8 * sl; }
          else { rel_w = B.k_free + 8 * sl; rel_wr = 0; }
        } else {
          const int sl = (vuse + (j == 7 ? 2 : j - 3)) % 3;
          mbar_wait(B.vw_full + 8 * sl, (vwph >> sl) & 1);
          vwph ^= 1u << sl;
          wa = sb + A_V + sl * 2 * AT + w * AT;
          rel_w = B.v_free + 8 * sl; rel_wr = 0;
        }
      };
      uint32_t xa, wa, rx, rw, rwr, prx, prw, prwr;
      if (r == DBGR && warp_in_wg == 0 && lane == 0) DSTAMP(w * 10 + 8);
      step(0, xa, wa, prx, prw, prwr);
      if (r == DBGR && warp_in_wg == 0 && lane == 0) DSTAMP(w * 10);
      PH(0);
      wg_fence();
      mma_kblock_mn<true>(acc, mkdesc(wa), mkdesc(xa));
      wg_commit();
      if (r > 1 && w == 1) flush_l();
#pragma unroll
      for (int j = 1; j < 8; j++) {
        step(j, xa, wa, rx, rw, rwr);
        if (r == DBGR && warp_in_wg == 0 && lane == 0) DSTAMP(w * 10 + j);
        PH(0);
        wg_fence();
        mma_kblock_mn<false>(acc, mkdesc(wa), mkdesc(xa));
        wg_commit();
        wg_wait<1>();
        if (lane == 0) { mbar_arrive(prw); if (prwr) mbar_arrive_remote(prwr); if (prx) mbar_arrive(prx); }
        prx = rx; prw = rw; prwr = rwr;
        PH(1);
      }
      wg_wait<0>();
      if (lane == 0) { mbar_arrive(prw); mbar_arrive(prx); mbar_arrive(B.b_empty);   }
      SSTAMP(1);
      mbar_wait(B.xq_done, r & 1);
      store_tile_scaled(acc, sb + A_Q + w * BT + st_off, qscale);
      fence_async_smem();
      __syncwarp();
      if (lane == 0) mbar_arrive(B.q_ready);
      mbar_wait(B.q_ready, r & 1);
      SSTAMP(2);
      PH(2);
    }
#pragma unroll 1
    for (int t = w; t < 8; t += 2) {
      const int kslot = (kuse + 5 + t) % 3, slot = (t + 1) % 3;
      mbar_wait(B.k_full + 8 * n6, nph);
      n6 += 2;
      if (n6 >= 6) { n6 -= 6; nph ^= 1; }
      PH(3);
      {
        const desc_t da = mkdesc(sb + A_K + kslot * 2 * AT), db = mkdesc(sb + A_Q);
        wg_fence();
        wgmma144<0, true>(acc, da, db);
#pragma unroll
        for (int kk = 1; kk < 8; kk++)
          wgmma144<0, false>(acc, da + (kk >> 2) * (AT >> 4) + (kk & 3) * 2, db + (kk >> 2) * (BT >> 4) + (kk & 3) * 2);
        wg_commit();
      }
      mbar_wait(B.b_empty + 8 * slot, (((4 + t) / 3) & 1) ^ 1);
      wg_wait<0>();
      if (lane == 0) {
        if (warp_in_wg == 0) *(volatile uint32_t*)(smem + A_BAR + 408 + 4 * w) = 4 * r + (t >> 1) + 1;
        if (t < 5) mbar_arrive2(B.k_free + 8 * kslot);
        else if (r + 1 < nheads) { mbar_arrive2(B.k_empty + 8 * kslot); mbar_arrive2_remote(rk_empty + 8 * kslot); }
        if (t >= 6) mbar_arrive(B.s_done);
      }
      mbar_wait(my_turn, tph);
      tph ^= 1;
      const uint32_t pa = sb + A_P + slot * BT + st_off;
#pragma unroll
      for (int j = 0; j < 18; j += 2) {
        float* e = &acc[4 * j];
#pragma unroll
        for (int i = 0; i < 8; i++) e[i] = ex2(e[i]);
        l[2 * j] += e[0] + e[2];
        l[2 * j + 1] += e[1] + e[3];
        l[2 * j + 2] += e[4] + e[6];
        l[2 * j + 3] += e[5] + e[7];
        stsm_t4(pa + j * 1024, pack_bf16(e[0], e[1]), pack_bf16(e[2], e[3]), pack_bf16(e[4], e[5]), pack_bf16(e[6], e[7]));
        if (j == TURN_AT && lane == 0) mbar_arrive(other_turn);
      }
      fence_async_smem();
      __syncwarp();
      if (lane == 0) mbar_arrive(B.p_full + 8 * slot);
      PH(6);
    }
    kuse = (kuse + 13) % 3;
    vuse = (vuse + 11) % 3;
    SSTAMP(3);
    if (w == 0 || r == 0) flush_l();
  }
  if (w == 1 && nheads > 1) flush_l();
  PH_OUT(88 + 8 * w);
}

__device__ __forceinline__ void att_fallback(uint8_t* img, float* scr, const __nv_bfloat16* xb, const __nv_bfloat16* wq,
                                             const __nv_bfloat16* Kh, const __nv_bfloat16* Vh, int tid) {
  float* ps = scr;
  float* qs = scr + 512;
  float* red = scr + 640;
  const float qscale = 0.08838834764831845f * 1.4426950408889634f;
  for (int q = 0; q < SQ; q++) {
    float qa = 0.f;
    for (int k = 0; k < DM; k++) qa = fmaf(__bfloat162float(xb[q * DM + k]), __bfloat162float(wq[(size_t)k * (NH * DH) + tid]), qa);
    qs[tid] = __bfloat162float(__float2bfloat16(qa * qscale));
    named_bar(1, 128);
    float s[4], m = -INFINITY;
    for (int i = 0; i < 4; i++) {
      const __nv_bfloat16* kr = Kh + (size_t)(tid + 128 * i) * DH;
      float a = 0.f;
      for (int d = 0; d < DH; d++) a = fmaf(qs[d], __bfloat162float(kr[d]), a);
      s[i] = a;
      m = fmaxf(m, a);
    }
    for (int o = 16; o; o >>= 1) m = fmaxf(m, __shfl_xor_sync(0xffffffffu, m, o));
    if ((tid & 31) == 0) red[tid >> 5] = m;
    named_bar(1, 128);
    m = fmaxf(fmaxf(red[0], red[1]), fmaxf(red[2], red[3]));
    float sum = 0.f;
    for (int i = 0; i < 4; i++) {
      const float e = exp2f(s[i] - m);
      sum += e;
      ps[tid + 128 * i] = __bfloat162float(__float2bfloat16(e));
    }
    for (int o = 16; o; o >>= 1) sum += __shfl_xor_sync(0xffffffffu, sum, o);
    if ((tid & 31) == 0) red[4 + (tid >> 5)] = sum;
    named_bar(1, 128);
    sum = red[4] + red[5] + red[6] + red[7];
    float o = 0.f;
    for (int k = 0; k < SK; k++) o = fmaf(ps[k], __bfloat162float(Vh[(size_t)k * DH + tid]), o);
    const int off = (tid >> 6) * BT + q * 128 + (((((tid & 63) >> 3)) ^ (q & 7)) << 4) + (tid & 7) * 2;
    *(__nv_bfloat16*)(img + off) = __float2bfloat16(o / sum);
    named_bar(1, 128);
  }
}

__device__ __forceinline__ void att_o_epilogue(const Params& p, uint32_t sb, uint8_t* smem, const HeadList& hl, int r, int nheads,
                                               int warp_in_wg,
                                               int lane, float (&acc0)[72], float (&acc1)[72]) {
  const AttBars B(sb + A_BAR);
  const int tid = warp_in_wg * 32 + lane;
  const uint32_t st_off = stsm_lane_off(warp_in_wg, lane);
  {
    EP(0);
    mbar_wait(B.l_ready, r & 1);
    float* lp = (float*)(smem + A_L);
    bool bad;
    {
      float l0 = 0.f, l1 = 1.f;
#pragma unroll
      for (int i = 0; i < 8; i++) l0 += lp[i * SQ + tid];
      if (tid < 16) {
        l1 = 0.f;
#pragma unroll
        for (int i = 0; i < 8; i++) l1 += lp[i * SQ + 128 + tid];
      }
      bad = !(l0 >= 5.4e-20f && l0 <= 1.8e19f && l1 >= 5.4e-20f && l1 <= 1.8e19f);
      lp[tid] = __fdividef(1.f, l0);
      if (tid < 16) lp[128 + tid] = __fdividef(1.f, l1);
    }
    named_bar(1, 128);
    EP(1);
    const uint32_t img = sb + A_O + st_off;
    __nv_bfloat162 chk0 = __floats2bfloat162_rn(0.f, 0.f), chk1 = chk0, chk2 = chk0, chk3 = chk0;
    const __nv_bfloat162 zero2 = chk0;
    const float2* li2 = (const float2*)lp + (lane & 3);
    float2 sa = li2[0], sb2 = li2[4], sc = li2[8], sd = li2[12];
    uint32_t a[36], c[36];
#pragma unroll
    for (int j = 0; j < 18; j += 2) {
      const float4 s = make_float4(sa.x, sa.y, sb2.x, sb2.y);
      sa = sc; sb2 = sd;
      if (j + 4 < 18) { sc = li2[4 * (j + 4)]; sd = li2[4 * (j + 5)]; }
      a[2 * j] = pack_bf16(acc0[4 * j] * s.x, acc0[4 * j + 1] * s.y);
      a[2 * j + 1] = pack_bf16(acc0[4 * j + 2] * s.x, acc0[4 * j + 3] * s.y);
      a[2 * j + 2] = pack_bf16(acc0[4 * j + 4] * s.z, acc0[4 * j + 5] * s.w);
      a[2 * j + 3] = pack_bf16(acc0[4 * j + 6] * s.z, acc0[4 * j + 7] * s.w);
      c[2 * j] = pack_bf16(acc1[4 * j] * s.x, acc1[4 * j + 1] * s.y);
      c[2 * j + 1] = pack_bf16(acc1[4 * j + 2] * s.x, acc1[4 * j + 3] * s.y);
      c[2 * j + 2] = pack_bf16(acc1[4 * j + 4] * s.z, acc1[4 * j + 5] * s.w);
      c[2 * j + 3] = pack_bf16(acc1[4 * j + 6] * s.z, acc1[4 * j + 7] * s.w);
      chk0 = __hfma2(*(const __nv_bfloat162*)&a[2 * j], zero2, chk0); chk0 = __hfma2(*(const __nv_bfloat162*)&a[2 * j + 1], zero2, chk0);
      chk1 = __hfma2(*(const __nv_bfloat162*)&a[2 * j + 2], zero2, chk1); chk2 = __hfma2(*(const __nv_bfloat162*)&a[2 * j + 3], zero2, chk2);
      chk3 = __hfma2(*(const __nv_bfloat162*)&c[2 * j], zero2, chk3); chk1 = __hfma2(*(const __nv_bfloat162*)&c[2 * j + 1], zero2, chk1);
      chk2 = __hfma2(*(const __nv_bfloat162*)&c[2 * j + 2], zero2, chk2); chk3 = __hfma2(*(const __nv_bfloat162*)&c[2 * j + 3], zero2, chk3);
    }
    if (r + 1 < nheads) mbar_wait(B.xo_empty, (r + 1) & 1);
    else mbar_wait(B.o_empty, (r & 1) ^ 1);
#pragma unroll
    for (int j = 0; j < 18; j += 2) {
      stsm_t4(img + j * 1024, a[2 * j], a[2 * j + 1], a[2 * j + 2], a[2 * j + 3]);
      stsm_t4(img + BT + j * 1024, c[2 * j], c[2 * j + 1], c[2 * j + 2], c[2 * j + 3]);
    }
    const uint32_t chk = *(const uint32_t*)&chk0 | *(const uint32_t*)&chk1 | *(const uint32_t*)&chk2 | *(const uint32_t*)&chk3;
    bad = bad || ((chk & 0x7fff7fffu) != 0u);
    EP(4);
    uint32_t anybad;
    asm volatile("{\n.reg .pred p, q;\nsetp.ne.u32 p, %1, 0;\nbar.red.or.pred q, 1, 128, p;\nselp.u32 %0, 1, 0, q;\n}\n"
                 : "=r"(anybad)
                 : "r"((uint32_t)bad)
                 : "memory");
    EP(5);
    if (anybad) {
      const HeadId id = att_head(hl, r);
      const int blk = id.g >> 3;
      const size_t hoff = (size_t)((id.g & 7) * NH + id.h) * (SK * DH);
      att_fallback(smem + A_O, (float*)(smem + A_FB), p.X[blk] + (size_t)(id.g & 7) * SQ * DM, p.Wq[blk] + id.h * DH,
                   p.K[blk] + hoff, p.V[blk] + hoff, tid);
    }
    EP(6);
    fence_async_smem();
    __syncwarp();
    if (lane == 0) mbar_arrive(B.o_full);
    EP(7);
  }
}

__device__ __forceinline__ void op_producer(const Params& p, uint32_t sb, uint8_t* smem, int g, int ch, int rank, int warp, int lane) {
  const uint32_t full = sb + O_BAR, empty = full + 8 * O_NS;
  volatile uint32_t* nready = (volatile uint32_t*)(smem + O_BAR + 128);
  if (warp == 1) {
    uint32_t* f = &g_oflag[ch][g * NH + lane];
    bool seen = false;
    uint32_t cnt = 0, n = 0;
    while (cnt < NH) {
      if (!seen) {
        uint32_t v;
        asm volatile("ld.acquire.gpu.global.u32 %0, [%1];" : "=r"(v) : "l"(f) : "memory");
        if (v) {
          seen = true;
          asm volatile("st.relaxed.gpu.global.u32 [%0], %1;" ::"l"(f), "r"(0u) : "memory");
        }
      }
      const uint32_t m = __ballot_sync(0xffffffffu, seen);
      const uint32_t c = m == 0xffffffffu ? 32u : (uint32_t)(__ffs(~m) - 1);
      if (c != cnt) {
        cnt = c;
        __syncwarp();
        if (lane == 0) {
          asm volatile("fence.acq_rel.cta;" ::: "memory");
          *nready = c;
        }
      } else {
        if (++n > (1u << 24)) __trap();
        __nanosleep(40);
      }
    }
    return;
  }
  if (warp != 0 || lane != 0) return;
  const int blk = g >> 3;
  int slot = 0;
  uint32_t ph = 1, have = 0;
  for (int kb = 0; kb < 64; kb++) {
    const int hh = g * NH + (kb >> 1);
    mbar_wait(empty + 8 * slot, ph);
    if (kb >= 40 && kb < 48) DSTAMP(44 + kb - 40);
    mbar_expect_tx(full + 8 * slot, O_STG);
    tma3d_mc(sb + slot * O_STG + rank * 2 * AT, &p.tmWo[blk], 0, kb * 64, ch * 4 + rank * 2, full + 8 * slot);
    if ((uint32_t)(kb >> 1) >= have) {
      uint32_t n = 0;
      while ((have = *nready) <= (uint32_t)(kb >> 1)) {
        if (++n > (1u << 26)) __trap();
      }
      asm volatile("fence.acq_rel.cta;" ::: "memory");
    }
    if ((kb & 1) == 0) TSTAMP(1 + (kb >> 1));
    bulk_load(sb + slot * O_STG + 4 * AT, g_O + (size_t)hh * QIMG + (kb & 1) * BT, BT, full + 8 * slot);
    if (++slot == O_NS) { slot = 0; ph ^= 1; }
  }
}
__device__ __forceinline__ void op_store_tile(const Params& p, uint32_t sb, int g, int ch, int m, const float (&acc)[72], int warp_in_wg,
                                              int lane) {
  store_tile_scaled(acc, sb + m * BT + stsm_lane_off(warp_in_wg, lane), 1.f);
}
__device__ __forceinline__ void op_issue_store(const Params& p, uint32_t sb, int g, int ch, int m) {
  tma2d_store(&p.tmOut, sb + m * BT, (g >> 3) * DM + ch * 256 + m * 64, (g & 7) * SQ);
}
__device__ __forceinline__ void op_consumer1(const Params& p, uint32_t sb, int g, int ch, int rank, int m0, int warp_in_wg,
                                             int lane) {
  const uint32_t full = sb + O_BAR, empty = full + 8 * O_NS, rempty = peer_addr(empty, rank ^ 1);
  float acc0[72];
  int slot = 1, prev = 0;
  uint32_t ph = 0;
  mbar_wait(full, 0);
  wg_fence();
  mma_kblock_mn<true>(acc0, mkdesc(sb + m0 * AT), mkdesc(sb + 4 * AT));
  wg_commit();
  for (int kb = 1; kb < 64; kb++) {
    mbar_wait(full + 8 * slot, ph);
    if (m0 == 0 && warp_in_wg == 0 && lane == 0 && kb >= 40 && kb < 48) DSTAMP(0 + kb - 40);
    wg_fence();
    mma_kblock_mn<false>(acc0, mkdesc(sb + slot * O_STG + m0 * AT), mkdesc(sb + slot * O_STG + 4 * AT));
    wg_commit();
    wg_wait<1>();
    if (lane == 0 && kb - 1 + O_NS < 64) { mbar_arrive(empty + 8 * prev); mbar_arrive_remote(rempty + 8 * prev); }
    prev = slot;
    if (++slot == O_NS) { slot = 0; ph ^= 1; }
  }
  wg_wait<0>();
  named_bar(2, 384);
  op_store_tile(p, sb, g, ch, m0, acc0, warp_in_wg, lane);
  fence_async_smem();
  named_bar(3 + m0, 128);
  if (warp_in_wg == 0 && lane == 0) {
    op_issue_store(p, sb, g, ch, m0);
    bulk_commit();
    bulk_wait_read();
  }
}

__device__ __forceinline__ void wg3_role(const Params& p, uint32_t sb, uint8_t* smem, bool is_att, int g, int idx, int rank,
                                         const HeadList& hl, int nheads, int warp_in_wg, int lane, float (&acc0)[72],
                                         float (&acc1)[72]) {
  if (is_att) {
    const AttBars B(sb + A_BAR);
    const uint32_t rv_empty = peer_addr(B.v_empty, rank ^ 1);
    PH_DECL;
    int slot = 0;
    uint32_t aph = 0;
    uint32_t bph = 0;
    auto sprio = [&](int r, int t) {
      volatile uint32_t* c = (volatile uint32_t*)(smem + A_BAR + 408 + 4 * (t & 1));
      const uint32_t need = 4 * r + ((t + 2) >> 1) + 1;
      uint32_t n = 0;
      while (*c < need && ++n < SPRIO) { }
    };
    for (int r = 0; r < nheads; r++) {
      int bslot = 1;
      {
        mbar_wait(B.v_full + 8 * slot, (aph >> slot) & 1);
        aph ^= 1u << slot;
        mbar_wait(B.p_full + 8 * bslot, (bph >> bslot) & 1);
        bph ^= 1u << bslot;
        sprio(r, 0);
        wg_fence();
        mma_kblock_mn2<true>(acc0, acc1, mkdesc(sb + A_V + slot * 2 * AT), mkdesc(sb + A_P + bslot * BT));
        wg_commit();
        wg_wait<0>();
        if (lane == 0) { mbar_arrive2(B.b_empty + 8 * bslot); mbar_arrive2(B.v_free + 8 * slot); }
        if (++slot == 3) slot = 0;
        if (++bslot == 3) bslot = 0;
      }
      for (int t = 1; t < 8; t++) {
        PH(3);
        mbar_wait(B.v_full + 8 * slot, (aph >> slot) & 1);
        aph ^= 1u << slot;
        PH(0);
        mbar_wait(B.p_full + 8 * bslot, (bph >> bslot) & 1);
        bph ^= 1u << bslot;
        PH(1);
        if (t <= 5) sprio(r, t);
        wg_fence();
        mma_kblock_mn2<false>(acc0, acc1, mkdesc(sb + A_V + slot * 2 * AT), mkdesc(sb + A_P + bslot * BT));
        wg_commit();
        wg_wait<0>();
        if (lane == 0) {
          mbar_arrive2(B.b_empty + 8 * bslot);
          if (t < 5) mbar_arrive2(B.v_free + 8 * slot);
          else if (r + 1 < nheads) { mbar_arrive2(B.v_empty + 8 * slot); mbar_arrive2_remote(rv_empty + 8 * slot); }
        }
        PH(2);
        if (++slot == 3) slot = 0;
        if (++bslot == 3) bslot = 0;
      }
      PH(4);
      if (warp_in_wg == 0 && lane == 0) { CSTAMP(65 + r); TSTAMP(17 + r); }
      att_o_epilogue(p, sb, smem, hl, r, nheads, warp_in_wg, lane, acc0, acc1);
      if (warp_in_wg == 0 && lane == 0) CSTAMP(73 + r);
      PH(5);
    }
    PH_OUT(104);
  } else {
    const uint32_t full = sb + O_BAR, empty = full + 8 * O_NS, rempty = peer_addr(empty, rank ^ 1);
    int slot = 1, prev = 0;
    uint32_t ph = 0;
    mbar_wait(full, 0);
    wg_fence();
    mma_kblock_mn<true>(acc0, mkdesc(sb + 2 * AT), mkdesc(sb + 4 * AT));
    wg_commit();
    mma_kblock_mn<true>(acc1, mkdesc(sb + 3 * AT), mkdesc(sb + 4 * AT));
    wg_commit();
    for (int kb = 1; kb < 64; kb++) {
      mbar_wait(full + 8 * slot, ph);
      if (warp_in_wg == 0 && lane == 0 && kb >= 40 && kb < 48) DSTAMP(10 + kb - 40);
      const desc_t da = mkdesc(sb + slot * O_STG + 2 * AT), db = mkdesc(sb + slot * O_STG + 4 * AT);
      wg_fence();
      mma_kblock_mn<false>(acc0, da, db);
      wg_commit();
      wg_wait<1>();
      if (lane == 0 && kb - 1 + O_NS < 64) { mbar_arrive(empty + 8 * prev); mbar_arrive_remote(rempty + 8 * prev); }
      wg_fence();
      mma_kblock_mn<false>(acc1, da + (AT >> 4), db);
      wg_commit();
      prev = slot;
      if (++slot == O_NS) { slot = 0; ph ^= 1; }
    }
    wg_wait<0>();
    named_bar(2, 384);
    op_store_tile(p, sb, g, idx, 2, acc0, warp_in_wg, lane);
    op_store_tile(p, sb, g, idx, 3, acc1, warp_in_wg, lane);
    fence_async_smem();
    named_bar(5, 128);
    if (warp_in_wg == 0 && lane == 0) {
      op_issue_store(p, sb, g, idx, 2);
      op_issue_store(p, sb, g, idx, 3);
      bulk_commit();
      bulk_wait_read();
      TSTAMP(40);
    }
  }
}

__global__ void __launch_bounds__(NTHREADS, 1) fused_attn_kernel(const __grid_constant__ Params p) {
  extern __shared__ __align__(1024) uint8_t smem[];
  const uint32_t sb = smem_u32(smem);
  const int warp = __shfl_sync(0xffffffffu, threadIdx.x >> 5, 0), lane = threadIdx.x & 31;
  const int wg = warp >> 2, warp_in_wg = warp & 3;
  const int rank = blockIdx.x & 1;
  const int ps = gridDim.x >> 2;
  const int pslot = blockIdx.x >> 1;
  const int blk = pslot >= ps ? 1 : 0, pr = pslot - blk * ps;
  const bool is_op = (pr & 3) == 3 && pr < 32;
  int g = 0, idx = 0, nheads;
  HeadList hl;
  hl.blk = blk;
  hl.stride = p.natt;
  hl.full = p.natt + 16;
  if (is_op) {
    const int m = pr >> 2;
    g = blk * 8 + 2 * (m >> 1) + rank;
    idx = m & 1;
    hl.i0 = NEARLY + 2 * m + rank;
    hl.i2 = 0;
    nheads = OPH;
  } else {
    const int i = 2 * (pr - min((pr + 1) >> 2, 8)) + rank;
    idx = i;
    hl.i0 = i < NEARLY ? i : i + 16;
    hl.i2 = OPH * hl.full + i;
    nheads = OPH + (8 * NH - hl.i2 + p.natt - 1) / p.natt;
  }
  {
    const HeadId id = att_head(hl, 0);
    const int t = threadIdx.x;
    if (t < 288) lsu_prefetch((const uint8_t*)(blk ? p.X[1] : p.X[0]) + (size_t)((id.g & 7) * SQ + (t >> 1)) * (DM * 2) + (t & 1) * 128);
    else if (t < 480) lsu_prefetch((const uint8_t*)(blk ? p.Wq[1] : p.Wq[0]) + (size_t)(t - 288) * (NH * DH * 2) + (id.h * DH + rank * 64) * 2);
  }
  if (threadIdx.x == 32) {
    const AttBars B(sb + A_BAR);
    for (int i = 0; i < 6; i++) mbar_init(B.k_full + 8 * i, 1);
    for (int i = 0; i < 3; i++) {
      mbar_init(B.kw_full + 8 * i, 1); mbar_init(B.k_empty + 8 * i, 16); mbar_init(B.k_free + 8 * i, 8); mbar_init(B.v_free + 8 * i, 8);
      mbar_init(B.vw_full + 8 * i, 1); mbar_init(B.v_full + 8 * i, 1); mbar_init(B.v_empty + 8 * i, 16);
      mbar_init(B.x_full + 8 * i, 1); mbar_init(B.p_full + 8 * i, 4); mbar_init(B.b_empty + 8 * i, 8);
    }
    for (int i = 0; i < 2; i++) { mbar_init(B.xq_full + 8 * i, 1); mbar_init(B.xo_full + 8 * i, 1); }
    mbar_init(B.s_done, 8); mbar_init(B.xo_empty, 16); mbar_init(B.xq_empty, 8); mbar_init(B.xq_done, 8);
    mbar_init(B.q_ready, 8); mbar_init(B.l_ready, 8);
    mbar_init(B.o_full, 4); mbar_init(B.o_empty, 1);
    for (int i = 0; i < 8; i++) mbar_init(B.turn + 8 * i, 1);
    mbar_init(sb + A_BAR + 400, 1);
    *(volatile uint32_t*)(smem + A_BAR + 408) = 0;
    *(volatile uint32_t*)(smem + A_BAR + 412) = 0;
    asm volatile("fence.mbarrier_init.release.cluster;" ::: "memory");
  }
  if (threadIdx.x == 64) {
    for (int i = 0; i < 2; i++) {
      asm volatile("prefetch.tensormap [%0];" ::"l"(&p.tmK[i]) : "memory");
      asm volatile("prefetch.tensormap [%0];" ::"l"(&p.tmV[i]) : "memory");
      asm volatile("prefetch.tensormap [%0];" ::"l"(&p.tmWq[i]) : "memory");
      asm volatile("prefetch.tensormap [%0];" ::"l"(&p.tmX[i]) : "memory");
      asm volatile("prefetch.tensormap [%0];" ::"l"(&p.tmWo[i]) : "memory");
    }
  }
  asm volatile("barrier.cluster.arrive.release.aligned;\nbarrier.cluster.wait.acquire.aligned;" ::: "memory");
  if (threadIdx.x == 0) { TSTAMP(0); CSTAMP(64); }

  auto switch_role = [&](bool init) {
    named_bar(6, NTHREADS);
    if (init) {
      for (int i = 0; i < O_NS; i++) { mbar_init(sb + O_BAR + 8 * i, 1); mbar_init(sb + O_BAR + 8 * O_NS + 8 * i, 24); }
      *(volatile uint32_t*)(smem + O_BAR + 128) = 0;
      asm volatile("fence.mbarrier_init.release.cluster;" ::: "memory");
      const uint32_t sw = sb + A_BAR + 400;
      asm volatile("mbarrier.arrive.release.cluster.shared::cluster.b64 _, [%0];" ::"r"(peer_addr(sw, rank ^ 1)) : "memory");
      uint32_t ok, n = 0;
      do {
        asm volatile("{\n.reg .pred p;\nmbarrier.try_wait.parity.acquire.cluster.shared::cta.b64 p, [%1], 0;\nselp.u32 %0, 1, 0, p;\n}\n"
                     : "=r"(ok) : "r"(sw) : "memory");
        if (++n > WAIT_LIMIT) __trap();
      } while (!ok);
    }
    named_bar(7, NTHREADS);
  };
  const bool run_att = p.mode != 3, run_op = is_op && p.mode != 2;

  if (wg == 0) {
    asm volatile("setmaxnreg.dec.sync.aligned.u32 32;");
    if (run_att) att_producer(p, sb, hl, rank, nheads, warp, lane);
    if (run_op) {
      __syncwarp();
      switch_role(threadIdx.x == 0);
      op_producer(p, sb, smem, g, idx, rank, warp, lane);
    }
  } else if (wg == 3) {
    asm volatile("setmaxnreg.inc.sync.aligned.u32 176;");
    float acc0[72], acc1[72];
    const int ph0 = run_att ? 0 : 1, ph1 = run_op ? 2 : 1;
#pragma unroll 1
    for (int phase = ph0; phase < ph1; phase++) {
      if (phase == 1) switch_role(false);
      wg3_role(p, sb, smem, phase == 0, g, idx, rank, hl, nheads, warp_in_wg, lane, acc0, acc1);
    }
  } else {
    asm volatile("setmaxnreg.inc.sync.aligned.u32 152;");
    if (run_att) {
      if (!is_op) { const long long t0 = clock64(); const long long d = STAG_EXPR; while (clock64() - t0 < d) __nanosleep(100); }
      att_s_role(sb, smem, wg - 1, rank, nheads, warp_in_wg, lane);
    }
    if (run_op) {
      switch_role(false);
      op_consumer1(p, sb, g, idx, rank, wg - 1, warp_in_wg, lane);
    }
  }
}

typedef CUresult (*EncodeFn)(CUtensorMap*, CUtensorMapDataType, cuuint32_t, void*, const cuuint64_t*, const cuuint64_t*,
                             const cuuint32_t*, const cuuint32_t*, CUtensorMapInterleave, CUtensorMapSwizzle,
                             CUtensorMapL2promotion, CUtensorMapFloatOOBfill);

void make_map(EncodeFn enc, CUtensorMap* m, const void* ptr, int rank, const cuuint64_t* dims, const cuuint64_t* strides,
              const cuuint32_t* box) {
  const cuuint32_t es[3] = {1, 1, 1};
  CUresult r = enc(m, CU_TENSOR_MAP_DATA_TYPE_BFLOAT16, rank, const_cast<void*>(ptr), dims, strides, box, es,
                   CU_TENSOR_MAP_INTERLEAVE_NONE, CU_TENSOR_MAP_SWIZZLE_128B, L2PROMO,
                   CU_TENSOR_MAP_FLOAT_OOB_FILL_NONE);
  (void)r;
}

}

#define KERNEL_MODE_SEQ 0

extern "C" void kernel_launch(void* const* d_in, const int* in_sizes, int n_in, void* d_out, int out_size) {
  (void)in_sizes; (void)n_in; (void)out_size;
  void* fn = nullptr;
  cudaDriverEntryPointQueryResult qr;
  cudaGetDriverEntryPoint("cuTensorMapEncodeTiled", &fn, cudaEnableDefault, &qr);
  EncodeFn enc = (EncodeFn)fn;
  Params p;
  for (int blk = 0; blk < 2; blk++) {
    const void* x = d_in[blk * 5 + 0];
    const void* k = d_in[blk * 5 + 1];
    const void* v = d_in[blk * 5 + 2];
    const void* wq = d_in[blk * 5 + 3];
    const void* wo = d_in[blk * 5 + 4];
    {
      const cuuint64_t dims[3] = {64, (cuuint64_t)NBATCH * NH * SK, 2}, str[2] = {256, 128};
      const cuuint32_t box[3] = {64, 64, 2};
      make_map(enc, &p.tmK[blk], k, 3, dims, str, box);
      make_map(enc, &p.tmV[blk], v, 3, dims, str, box);
    }
    {
      const cuuint64_t dims[3] = {64, DM, (cuuint64_t)NH * 2}, str[2] = {NH * DH * 2, 128};
      const cuuint32_t box[3] = {64, 64, 1};
      make_map(enc, &p.tmWq[blk], wq, 3, dims, str, box);
    }
    {
      const cuuint64_t dims[3] = {64, (cuuint64_t)NH * DH, 8}, str[2] = {DM * 2, 128};
      const cuuint32_t box[3] = {64, 64, 2};
      make_map(enc, &p.tmWo[blk], wo, 3, dims, str, box);
    }
    {
      const cuuint64_t dims[2] = {DM, (cuuint64_t)NBATCH * SQ}, str[1] = {DM * 2};
      const cuuint32_t box[2] = {64, SQ};
      make_map(enc, &p.tmX[blk], x, 2, dims, str, box);
    }
    p.K[blk] = (const __nv_bfloat16*)k;
    p.V[blk] = (const __nv_bfloat16*)v;
    p.X[blk] = (const __nv_bfloat16*)x;
    p.Wq[blk] = (const __nv_bfloat16*)wq;
    p.Wo[blk] = (const __nv_bfloat16*)wo;
  }
  {
    const cuuint64_t dims[2] = {2 * DM, (cuuint64_t)NBATCH * SQ}, str[1] = {2 * DM * 2};
    const cuuint32_t box[2] = {64, SQ};
    make_map(enc, &p.tmOut, d_out, 2, dims, str, box);
  }
  cudaFuncSetAttribute(fused_attn_kernel, cudaFuncAttributeMaxDynamicSharedMemorySize, SMEM_BYTES);
  int nsm = 132;
  cudaDeviceGetAttribute(&nsm, cudaDevAttrMultiProcessorCount, 0);
  if (nsm > 132) nsm = 132;
  nsm &= ~3;
  p.natt = nsm / 2 - 16;
  cudaLaunchConfig_t cfg = {};
  cfg.gridDim = dim3(nsm);
  cfg.blockDim = dim3(NTHREADS);
  cfg.dynamicSmemBytes = SMEM_BYTES;
  cfg.stream = cudaStreamPerThread;
  cudaLaunchAttribute at[1];
  at[0].id = cudaLaunchAttributeClusterDimension;
  at[0].val.clusterDim.x = 2;
  at[0].val.clusterDim.y = 1;
  at[0].val.clusterDim.z = 1;
  cfg.attrs = at;
  cfg.numAttrs = 1;
  p.mode = 0;
  cudaLaunchKernelEx(&cfg, fused_attn_kernel, p);
}
```

```cpp
#include <cuda_runtime.h>
#include <cuda_bf16.h>
#include <cuda.h>
#include <stdint.h>
#define DBG_SYNC(tag)

namespace {

constexpr int NBATCH = 8, SQ = 144, DM = 512, NH = 32, DH = 128, SK = 512;
constexpr int NGRP = 16;
constexpr int BT = SQ * 128;
constexpr int AT = 64 * 128;
constexpr int QIMG = 2 * BT;
constexpr int NTHREADS = 512;
constexpr int SMEM_BYTES = 232448;
constexpr uint32_t WAIT_LIMIT = 1u << 20;
#define PUB_FIRST
#define PLAIN_EX2
#define L2PROMO CU_TENSOR_MAP_L2_PROMOTION_NONE
#define SIDE_THR 430
#define STAG_EXPR (idx < 40 ? (long long)(idx >> 1) * STAG_STEP : (long long)STAG_LAST)
#define STAG_STEP 600
#define STAG_LAST 14000
#define OPH 1
#define OSPLIT 9
#define SPRIO 60
#define KV_PFK 0
#define KV_PF0 1
#define KV_PFV 0
#define KV0_PF 0
#define KV0_AFTER 1
#define SSW 0
#define FLUSH_AT 0
#define VGATE 0
#define DBGR 2
#define NEARLY 0
#define NWK 5
#define CLUSTER 2
#define W_PF 0
#define TURN_AT 16
#define PF_DIST 0

constexpr int A_Q = 0;
constexpr int A_O = A_Q + QIMG;
constexpr int A_P = A_O + QIMG;
constexpr int A_K = A_P + 3 * BT;
constexpr int A_V = A_K + 3 * 2 * AT;
constexpr int A_L = A_V + 3 * 2 * AT;
constexpr int A_FB = A_L + SQ * 4;
constexpr int A_BAR = A_L + 8 * SQ * 4;
static_assert(A_BAR % 8 == 0 && A_BAR + 464 <= SMEM_BYTES - 16 && A_FB + 648 * 4 <= A_BAR, "att smem");
constexpr int O_NS = 4;
constexpr int O_STG = 4 * AT + BT;
constexpr int O_BAR = O_NS * O_STG;
static_assert(O_STG % 1024 == 0 && O_BAR + 256 <= SMEM_BYTES, "op smem");

struct alignas(64) Params {
  CUtensorMap tmK[2], tmV[2], tmWq[2], tmWo[2], tmX[2], tmOut;
  const __nv_bfloat16* K[2];
  const __nv_bfloat16* V[2];
  const __nv_bfloat16* X[2];
  const __nv_bfloat16* Wq[2];
  const __nv_bfloat16* Wo[2];
  int natt;
  int sidemap;
  int mode;
};

__device__ uint8_t g_O[NGRP * NH * QIMG];
__device__ uint32_t g_oflag[2][NGRP * NH];
__device__ uint32_t g_probe[64];
__device__ uint32_t g_ticket[2][32];
__device__ uint32_t g_done;

#define TSTAMP(i)
#define CSTAMP(i)
#define DSTAMP(i)
#define PH_DECL
#define PH(i)
#define PH_OUT(base)
#define EP(i)
__device__ __forceinline__ uint32_t smem_u32(const void* p) { return (uint32_t)__cvta_generic_to_shared(p); }
__device__ __forceinline__ void mbar_init(uint32_t bar, uint32_t cnt) {
  asm volatile("mbarrier.init.shared::cta.b64 [%0], %1;" ::"r"(bar), "r"(cnt) : "memory");
}
__device__ __forceinline__ void mbar_expect_tx(uint32_t bar, uint32_t bytes) {
  asm volatile("mbarrier.arrive.expect_tx.shared::cta.b64 _, [%0], %1;" ::"r"(bar), "r"(bytes) : "memory");
}
__device__ __forceinline__ void mbar_arrive(uint32_t bar) {
  asm volatile("mbarrier.arrive.shared::cta.b64 _, [%0];" ::"r"(bar) : "memory");
}
__device__ __forceinline__ void mbar_arrive2(uint32_t bar) {
  asm volatile("mbarrier.arrive.shared::cta.b64 _, [%0], 2;" ::"r"(bar) : "memory");
}
__device__ __forceinline__ uint32_t peer_addr(uint32_t addr, uint32_t peer) {
  uint32_t r;
  asm volatile("mapa.shared::cluster.u32 %0, %1, %2;" : "=r"(r) : "r"(addr), "r"(peer));
  return r;
}
__device__ __forceinline__ void mbar_arrive_remote(uint32_t rbar) {
  asm volatile("mbarrier.arrive.shared::cluster.b64 _, [%0];" ::"r"(rbar) : "memory");
}
__device__ __forceinline__ void mbar_arrive2_remote(uint32_t rbar) {
  asm volatile("mbarrier.arrive.shared::cluster.b64 _, [%0], 2;" ::"r"(rbar) : "memory");
}
__device__ __forceinline__ bool mbar_try(uint32_t bar, uint32_t parity) {
  uint32_t ok;
  asm volatile(
      "{\n.reg .pred p;\nmbarrier.try_wait.parity.shared::cta.b64 p, [%1], %2;\nselp.u32 %0, 1, 0, p;\n}\n"
      : "=r"(ok)
      : "r"(bar), "r"(parity)
      : "memory");
  return ok;
}
__device__ __forceinline__ void mbar_wait(uint32_t bar, uint32_t parity) {
  if (mbar_try(bar, parity)) return;
  uint32_t n = 0;
  while (!mbar_try(bar, parity)) {
    if (++n > WAIT_LIMIT) __trap();
  }
}
__device__ __forceinline__ void fence_async_smem() { asm volatile("fence.proxy.async.shared::cta;" ::: "memory"); }
__device__ __forceinline__ void fence_async_all() { asm volatile("fence.proxy.async;" ::: "memory"); }
__device__ __forceinline__ void named_bar(int id, int n) { asm volatile("bar.sync %0, %1;" ::"r"(id), "r"(n) : "memory"); }

__device__ __forceinline__ uint64_t policy_evict_first() {
  uint64_t p;
  asm volatile("createpolicy.fractional.L2::evict_first.b64 %0, 1.0;" : "=l"(p));
  return p;
}
__device__ __forceinline__ void tma2d(uint32_t dst, const CUtensorMap* tm, int c0, int c1, uint32_t bar) {
  asm volatile("cp.async.bulk.tensor.2d.shared::cluster.global.mbarrier::complete_tx::bytes [%0], [%1, {%3, %4}], [%2];" ::"r"(dst),
               "l"(tm), "r"(bar), "r"(c0), "r"(c1)
               : "memory");
}
__device__ __forceinline__ void tma3d(uint32_t dst, const CUtensorMap* tm, int c0, int c1, int c2, uint32_t bar) {
  asm volatile("cp.async.bulk.tensor.3d.shared::cluster.global.mbarrier::complete_tx::bytes [%0], [%1, {%3, %4, %5}], [%2];" ::"r"(dst),
               "l"(tm), "r"(bar), "r"(c0), "r"(c1), "r"(c2)
               : "memory");
}
__device__ __forceinline__ void tma3d_mc(uint32_t dst, const CUtensorMap* tm, int c0, int c1, int c2, uint32_t bar) {
  asm volatile(
      "cp.async.bulk.tensor.3d.shared::cluster.global.mbarrier::complete_tx::bytes.multicast::cluster [%0], [%1, {%3, %4, %5}], [%2], %6;" ::"r"(dst),
      "l"(tm), "r"(bar), "r"(c0), "r"(c1), "r"(c2), "h"((uint16_t)3)
      : "memory");
}
__device__ __forceinline__ void tma3d_hint(uint32_t dst, const CUtensorMap* tm, int c0, int c1, int c2, uint32_t bar, uint64_t pol) {
  asm volatile(
      "cp.async.bulk.tensor.3d.shared::cluster.global.mbarrier::complete_tx::bytes.L2::cache_hint [%0], [%1, {%3, %4, %5}], [%2], %6;" ::"r"(dst),
      "l"(tm), "r"(bar), "r"(c0), "r"(c1), "r"(c2), "l"(pol)
      : "memory");
}
__device__ __forceinline__ void tma2d_prefetch(const CUtensorMap* tm, int c0, int c1) {
  asm volatile("cp.async.bulk.prefetch.tensor.2d.L2.global [%0, {%1, %2}];" ::"l"(tm), "r"(c0), "r"(c1) : "memory");
}
__device__ __forceinline__ void tma3d_prefetch(const CUtensorMap* tm, int c0, int c1, int c2) {
  asm volatile("cp.async.bulk.prefetch.tensor.3d.L2.global [%0, {%1, %2, %3}];" ::"l"(tm), "r"(c0), "r"(c1), "r"(c2) : "memory");
}
__device__ __forceinline__ void bulk_load(uint32_t dst, const void* src, uint32_t bytes, uint32_t bar) {
  asm volatile("cp.async.bulk.shared::cluster.global.mbarrier::complete_tx::bytes [%0], [%1], %2, [%3];" ::"r"(dst), "l"(src),
               "r"(bytes), "r"(bar)
               : "memory");
}
__device__ __forceinline__ void bulk_store(void* dst, uint32_t src, uint32_t bytes) {
  asm volatile("cp.async.bulk.global.shared::cta.bulk_group [%0], [%1], %2;" ::"l"(dst), "r"(src), "r"(bytes) : "memory");
}
__device__ __forceinline__ void tma2d_store(const CUtensorMap* tm, uint32_t src, int c0, int c1) {
  asm volatile("cp.async.bulk.tensor.2d.global.shared::cta.bulk_group [%0, {%2, %3}], [%1];" ::"l"(tm), "r"(src), "r"(c0), "r"(c1)
               : "memory");
}
__device__ __forceinline__ void bulk_commit() { asm volatile("cp.async.bulk.commit_group;" ::: "memory"); }
__device__ __forceinline__ void bulk_wait_read() { asm volatile("cp.async.bulk.wait_group.read 0;" ::: "memory"); }
__device__ __forceinline__ void bulk_wait_all() { asm volatile("cp.async.bulk.wait_group 0;" ::: "memory"); }
__device__ __forceinline__ void l2_prefetch(const void* src, uint32_t bytes, uint64_t pol) {
  asm volatile("cp.async.bulk.prefetch.L2.global.L2::cache_hint [%0], %1, %2;" ::"l"(src), "r"(bytes), "l"(pol) : "memory");
}
__device__ __forceinline__ void tlb_warm(const void* a) {
  asm volatile("cp.async.bulk.prefetch.L2.global [%0], 128;" ::"l"(a) : "memory");
}
__device__ __forceinline__ void lsu_prefetch(const void* a) { asm volatile("prefetch.global.L2 [%0];" ::"l"(a)); }
__device__ __forceinline__ void flag_add_release(uint32_t* f) {
  asm volatile("red.release.gpu.global.add.u32 [%0], 1;" ::"l"(f) : "memory");
}
__device__ __forceinline__ void flag_wait_reset(uint32_t* f, uint32_t target) {
  uint32_t v, n = 0;
  while (true) {
    asm volatile("ld.acquire.gpu.global.u32 %0, [%1];" : "=r"(v) : "l"(f) : "memory");
    if (v >= target) break;
    if (++n > (1u << 24)) __trap();
    __nanosleep(20);
  }
  asm volatile("st.relaxed.gpu.global.u32 [%0], %1;" ::"l"(f), "r"(0u) : "memory");
  fence_async_all();
}

__device__ __forceinline__ void wg_fence() { asm volatile("wgmma.fence.sync.aligned;" ::: "memory"); }
__device__ __forceinline__ void wg_commit() { asm volatile("wgmma.commit_group.sync.aligned;" ::: "memory"); }
template <int N>
__device__ __forceinline__ void wg_wait() {
  asm volatile("wgmma.wait_group.sync.aligned %0;" ::"n"(N) : "memory");
}
typedef uint32_t desc_t;
__device__ __forceinline__ desc_t mkdesc(uint32_t addr) { return ((addr & 0x3FFFF) >> 4) | (1u << 16); }

#define ACC8(c, o) c(d[o]), c(d[o + 1]), c(d[o + 2]), c(d[o + 3]), c(d[o + 4]), c(d[o + 5]), c(d[o + 6]), c(d[o + 7])
#define ACC72(c) ACC8(c, 0), ACC8(c, 8), ACC8(c, 16), ACC8(c, 24), ACC8(c, 32), ACC8(c, 40), ACC8(c, 48), ACC8(c, 56), ACC8(c, 64)
#define WGMMA144_HEAD                                                                                                          \
  "wgmma.mma_async.sync.aligned.m64n144k16.f32.bf16.bf16 "                                                                     \
  "{%0, %1, %2, %3, %4, %5, %6, %7, %8, %9, %10, %11, %12, %13, %14, %15, %16, %17, %18, %19, %20, %21, %22, %23, "            \
  "%24, %25, %26, %27, %28, %29, %30, %31, %32, %33, %34, %35, %36, %37, %38, %39, %40, %41, %42, %43, %44, %45, %46, %47, "   \
  "%48, %49, %50, %51, %52, %53, %54, %55, %56, %57, %58, %59, %60, %61, %62, %63, %64, %65, %66, %67, %68, %69, %70, %71}, "
template <int TA, bool INIT>
__device__ __forceinline__ void wgmma144(float (&d)[72], desc_t da, desc_t db) {
  if constexpr (INIT) {
    asm volatile("{\n.reg .pred p;\n.reg .b64 da, db;\n.reg .b32 hi;\nmov.b32 hi, 0x40000040;\nmov.b64 da, {%72, hi};\n"
                 "mov.b64 db, {%73, hi};\nsetp.ne.b32 p, 0, 0;\n" WGMMA144_HEAD "da, db, p, 1, 1, %74, 0;\n}\n"
                 : ACC72("=f")
                 : "r"(da), "r"(db), "n"(TA));
  } else {
    asm volatile("{\n.reg .pred p;\n.reg .b64 da, db;\n.reg .b32 hi;\nmov.b32 hi, 0x40000040;\nmov.b64 da, {%72, hi};\n"
                 "mov.b64 db, {%73, hi};\nsetp.eq.b32 p, 0, 0;\n" WGMMA144_HEAD "da, db, p, 1, 1, %74, 0;\n}\n"
                 : ACC72("+f")
                 : "r"(da), "r"(db), "n"(TA));
  }
}
template <bool INIT>
__device__ __forceinline__ void mma_kblock_mn(float (&d)[72], desc_t da, desc_t db) {
  wgmma144<1, INIT>(d, da, db);
  wgmma144<1, false>(d, da + 128, db + 2);
  wgmma144<1, false>(d, da + 256, db + 4);
  wgmma144<1, false>(d, da + 384, db + 6);
}
template <bool INIT>
__device__ __forceinline__ void mma_kblock_mn2(float (&d0)[72], float (&d1)[72], desc_t da, desc_t db) {
  wgmma144<1, INIT>(d0, da, db);
  wgmma144<1, INIT>(d1, da + (AT >> 4), db);
#pragma unroll
  for (int kk = 1; kk < 4; kk++) {
    wgmma144<1, false>(d0, da + kk * 128, db + kk * 2);
    wgmma144<1, false>(d1, da + kk * 128 + (AT >> 4), db + kk * 2);
  }
}
__device__ __forceinline__ uint32_t pack_bf16(float lo, float hi) {
  uint32_t r;
  asm("cvt.rn.bf16x2.f32 %0, %1, %2;" : "=r"(r) : "f"(hi), "f"(lo));
  return r;
}
__device__ __forceinline__ void stsm_t4(uint32_t addr, uint32_t r0, uint32_t r1, uint32_t r2, uint32_t r3) {
  asm volatile("stmatrix.sync.aligned.m8n8.x4.trans.shared.b16 [%0], {%1, %2, %3, %4};" ::"r"(addr), "r"(r0), "r"(r1), "r"(r2),
               "r"(r3)
               : "memory");
}
__device__ __forceinline__ float ex2(float x) {
  float y;
  asm volatile("ex2.approx.ftz.f32 %0, %1;" : "=f"(y) : "f"(x));
  return y;
}
__device__ __forceinline__ void ex2x8_dep(float* x, uint32_t dep) {
  asm volatile(
      "{\n.reg .pred p;\nsetp.ne.u32 p, %8, 0xFFFFFFFF;\n"
      "@p ex2.approx.ftz.f32 %0, %0;\n@p ex2.approx.ftz.f32 %1, %1;\n@p ex2.approx.ftz.f32 %2, %2;\n@p ex2.approx.ftz.f32 %3, %3;\n"
      "@p ex2.approx.ftz.f32 %4, %4;\n@p ex2.approx.ftz.f32 %5, %5;\n@p ex2.approx.ftz.f32 %6, %6;\n@p ex2.approx.ftz.f32 %7, %7;\n}\n"
      : "+f"(x[0]), "+f"(x[1]), "+f"(x[2]), "+f"(x[3]), "+f"(x[4]), "+f"(x[5]), "+f"(x[6]), "+f"(x[7])
      : "r"(dep));
}
__device__ __forceinline__ uint32_t stsm_lane_off(int warp_in_wg, int lane) {
  int mi = lane >> 3, rr = lane & 7;
  return (uint32_t)(((mi >> 1) * 8 + rr) * 128 + (((2 * warp_in_wg + (mi & 1)) ^ rr) << 4));
}
__device__ __forceinline__ void store_tile_scaled(const float (&d)[72], uint32_t base, float s) {
#pragma unroll
  for (int j = 0; j < 18; j += 2) {
    stsm_t4(base + j * 1024, pack_bf16(d[4 * j] * s, d[4 * j + 1] * s), pack_bf16(d[4 * j + 2] * s, d[4 * j + 3] * s),
            pack_bf16(d[4 * j + 4] * s, d[4 * j + 5] * s), pack_bf16(d[4 * j + 6] * s, d[4 * j + 7] * s));
  }
}

struct AttBars {
  uint32_t kw_full, k_full, k_empty, vw_full, v_full, v_empty, x_full, p_full, b_empty, xq_full, xo_full, s_done, xo_empty, q_ready,
      l_ready, li_ready, o_full, o_empty, turn, xq_empty, xq_done, k_free, v_free;
  __device__ __forceinline__ AttBars(uint32_t b)
      : kw_full(b), k_full(b + 24), k_empty(b + 72), vw_full(b + 96), v_full(b + 120), v_empty(b + 144), x_full(b + 168),
        p_full(b + 192), b_empty(b + 216), xq_full(b + 240), xo_full(b + 256), s_done(b + 272), xo_empty(b + 280),
        q_ready(b + 288), l_ready(b + 296), li_ready(b + 304), o_full(b + 312), o_empty(b + 320), turn(b + 328), xq_empty(b + 304), xq_done(b + 392), k_free(b + 416), v_free(b + 440) {}
};
constexpr int ATT_BAR_BYTES = 400;
struct HeadList { int blk, i0, i2, full, stride; };
struct HeadId { int g, h; };
__device__ __forceinline__ HeadId att_head(const HeadList& hl, int r) {
  const int hi = r < OPH ? hl.i0 + r * hl.full : hl.i2 + (r - OPH) * hl.stride;
  return {hl.blk * 8 + (hi & 7), hi >> 3};
}
#define KVROW(id) ((((id).g & 7) * NH + (id).h) * SK)

__device__ __forceinline__ void att_producer(const Params& p, uint32_t sb, const HeadList& hl, int rank, int nheads, int warp,
                                             int lane) {
  const AttBars B(sb + A_BAR);
  if (lane != 0 && warp != 3) return;
  if (warp == 0 || warp == 1) {
    const bool isk = warp == 0;
    const int nw = isk ? 5 : 3;
    const uint32_t wlist = isk ? 0x65210u : 0x743u;
    const uint32_t base = sb + (isk ? A_K : A_V), empty = isk ? B.k_empty : B.v_empty, wfull = isk ? B.kw_full : B.vw_full;
    const uint64_t pol = policy_evict_first();
    int slot = 0, n6 = 0;
    const uint32_t lfree = isk ? B.k_free : B.v_free;
    uint32_t eph = 0, fph = 0;
    int used = 0;
    for (int r = 0; r < nheads; r++) {
      const HeadId id = att_head(hl, r);
      const int blk = id.g >> 3;
      for (int j = 0; j < nw + 8; j++) {
        const uint32_t dst = base + slot * 2 * AT;
        if (used >= 3) {
          if (j < nw) { mbar_wait(empty + 8 * slot, (eph >> slot) & 1); eph ^= 1u << slot; }
          else { mbar_wait(lfree + 8 * slot, (fph >> slot) & 1); fph ^= 1u << slot; }
        }
        used++;
        if (r == 0 && j < 3) {
          if (isk) { if (j > 0) mbar_wait(B.kw_full + 8 * (j - 1), 0); }
          else mbar_wait(B.kw_full + 8 * (j == 0 ? 0 : (j == 1 ? 1 : 2)), 0);
        }
        if (j < nw) {
          const int wj = (wlist >> (4 * j)) & 15;
          if (r == DBGR) DSTAMP(20 + wj);
          mbar_expect_tx(wfull + 8 * slot, 2 * AT);
          tma3d_mc(dst + rank * AT, &p.tmWq[blk], 0, wj * 64, id.h * 2 + rank, wfull + 8 * slot);
        } else {
          if (VGATE && !isk && j == nw) mbar_wait(VGATE == 1 ? B.xq_empty : B.xq_done, r & 1);
          const uint32_t full = isk ? B.k_full + 8 * n6 : B.v_full + 8 * slot;
          mbar_expect_tx(full, 2 * AT);
          tma3d_hint(dst, isk ? &p.tmK[blk] : &p.tmV[blk], 0, KVROW(id) + (j - nw) * 64, 0, full, pol);
          if (++n6 == 6) n6 = 0;
        }
        if (++slot == 3) slot = 0;
      }
    }
  } else if (warp == 2) {
    int slot = 0;
    uint32_t ph = 1;
    for (int r = 0; r < nheads; r++) {
      const HeadId id = att_head(hl, r);
      const CUtensorMap* tm = &p.tmX[id.g >> 3];
      const int row = (id.g & 7) * SQ;
      auto load_x = [&](int j, uint32_t dst, uint32_t bar) {
        if (r == DBGR) DSTAMP(30 + j);
        mbar_expect_tx(bar, BT);
        tma2d(dst, tm, j * 64, row, bar);
      };
      auto load_b = [&](int j) {
        mbar_wait(B.b_empty + 8 * slot, ph);
        load_x(j, sb + A_P + slot * BT, B.x_full + 8 * slot);
        if (++slot == 3) { slot = 0; ph ^= 1; }
      };
      if (r == 0) {
        load_x(0, sb + A_O, B.xo_full);
        load_x(1, sb + A_O + BT, B.xo_full + 8);
        mbar_wait(B.xo_full, 0);
      } else {
        mbar_wait(B.s_done, (r - 1) & 1);
      }
      load_x(2, sb + A_Q, B.xq_full);
      if (r == 0) mbar_wait(B.xo_full + 8, 0);
      load_x(3, sb + A_Q + BT, B.xq_full + 8);
      if (r == 0) mbar_wait(B.xq_full, 0);
      load_b(4);
      if (r == 0) mbar_wait(B.xq_full + 8, 0);
      load_b(5);
      mbar_wait(B.xq_empty, (r & 1));
      load_x(6, sb + A_Q, B.xq_full);
      load_b(7);
      mbar_wait(B.b_empty + 8 * slot, ph);
      if (++slot == 3) { slot = 0; ph ^= 1; }
      for (int t = 0; t < 8; t++) {
        mbar_wait(B.b_empty + 8 * slot, ph);
        if (++slot == 3) { slot = 0; ph ^= 1; }
      }
    }
  } else {
    auto prefetch_w = [&](int r) {
      const HeadId id = att_head(hl, r);
      const uint8_t* src = (const uint8_t*)((id.g >> 3) ? p.Wq[1] : p.Wq[0]) + (id.h * DH + rank * 64) * 2 + (size_t)lane * (NH * DH * 2);
#pragma unroll 4
      for (int k = 0; k < 16; k++) lsu_prefetch(src + (size_t)k * 32 * (NH * DH * 2));
    };
    auto load_x01 = [&](int r) {
      const HeadId nx = att_head(hl, r);
      for (int j = 0; j < 2; j++) {
        if (r == DBGR) DSTAMP(30 + j);
        mbar_expect_tx(B.xo_full + 8 * j, BT);
        tma2d(sb + A_O + j * BT, &p.tmX[nx.g >> 3], j * 64, (nx.g & 7) * SQ, B.xo_full + 8 * j);
      }
    };
    if (W_PF == 1 && nheads > 1) prefetch_w(1);
    if (lane == 0 && nheads > 1) {
      mbar_wait(B.xo_empty, 0);
      load_x01(1);
    }
    auto prefetch_kv = [&](int r) {
      const HeadId id = att_head(hl, r);
      const size_t off = (size_t)KVROW(id) * (DH * 2) + lane * 128;
      const uint8_t* k = (const uint8_t*)((id.g >> 3) ? p.K[1] : p.K[0]) + off;
      const uint8_t* v = (const uint8_t*)((id.g >> 3) ? p.V[1] : p.V[0]) + off;
#pragma unroll 4
      for (int i = 4 * KV_PF0; i < 4 * KV_PFK; i++) lsu_prefetch(k + i * 4096);
#pragma unroll 4
      for (int i = 0; i < 4 * KV_PFV; i++) lsu_prefetch(v + i * 4096);
    };
    for (int r = 0; r < nheads; r++) {
      if (KV_PFK > 0 && r + 1 < nheads) {
        if (lane == 0) mbar_wait(B.s_done, r & 1);
        __syncwarp();
        prefetch_kv(r + 1);
      }
      if (lane == 0) {
        const HeadId id = att_head(hl, r);
        const int hh = id.g * NH + id.h;
        mbar_wait(B.o_full, r & 1);
        if (r < 2) DSTAMP(40 + 0 + 4 * r + 2);
#pragma unroll
        for (int c = 0; c < OSPLIT; c++) bulk_store(g_O + (size_t)hh * QIMG + c * (QIMG / OSPLIT), sb + A_O + c * (QIMG / OSPLIT), QIMG / OSPLIT);
        bulk_commit();
        bulk_wait_read();
        if (r < 2) DSTAMP(40 + 1 + 4 * r + 2);
        mbar_arrive(B.o_empty);
        if (r + 2 < nheads) load_x01(r + 2);
        bulk_wait_all();
        if (r < 2) DSTAMP(40 + 2 + 4 * r + 2);
        asm volatile("red.relaxed.gpu.global.add.u32 [%0], 1;" ::"l"(&g_oflag[0][hh]) : "memory");
        asm volatile("red.relaxed.gpu.global.add.u32 [%0], 1;" ::"l"(&g_oflag[1][hh]) : "memory");
        if (r < 2) DSTAMP(40 + 3 + 4 * r + 2);
        TSTAMP(9 + r);
      }
      __syncwarp();
      if (W_PF == 1 && r + 2 < nheads) prefetch_w(r + 2);
    }
  }
}

__device__ __forceinline__ void att_s_role(uint32_t sb, uint8_t* smem, int w, int rank, int nheads, int delay, int warp_in_wg,
                                           int lane) {
  const AttBars B(sb + A_BAR);
  const uint32_t rk_empty = peer_addr(B.k_empty, rank ^ 1);
  const uint32_t st_off = stsm_lane_off(warp_in_wg, lane);
  const float qscale = 0.08838834764831845f * 1.4426950408889634f;
  float acc[72], l[36];
#pragma unroll
  for (int i = 0; i < 36; i++) l[i] = 0.f;
  const uint32_t my_turn = B.turn + 8 * (w * 4 + warp_in_wg), other_turn = B.turn + 8 * ((w ^ 1) * 4 + warp_in_wg);
  uint32_t tph = w ^ 1;
  uint32_t kwph = 0, vwph = 0;
  int kuse = 0, vuse = 0;
  int n6 = w;
  uint32_t nph = 0;
  auto flush_l = [&]() {
      float v[18], u[10];
      const bool b4 = lane & 16, b3 = lane & 8, b2 = lane & 4;
#pragma unroll
      for (int i = 0; i < 18; i++) {
        const float keep = b4 ? l[i + 18] : l[i], send = b4 ? l[i] : l[i + 18];
        v[i] = keep + __shfl_xor_sync(0xffffffffu, send, 16);
      }
#pragma unroll
      for (int i = 0; i < 9; i++) {
        const float keep = b3 ? v[i + 9] : v[i], send = b3 ? v[i] : v[i + 9];
        u[i] = keep + __shfl_xor_sync(0xffffffffu, send, 8);
      }
      u[9] = 0.f;
      float* lp = (float*)(smem + A_L) + (w * 4 + warp_in_wg) * SQ + 2 * (lane & 3);
      const int ibase = (b4 ? 18 : 0) + (b3 ? 9 : 0) + (b2 ? 5 : 0);
#pragma unroll
      for (int i = 0; i < 5; i++) {
        const float keep = b2 ? u[i + 5] : u[i], send = b2 ? u[i] : u[i + 5];
        const float sum = keep + __shfl_xor_sync(0xffffffffu, send, 4);
        const int idx = ibase + i;
        if (!(b2 && i == 4)) lp[8 * (idx >> 1) + (idx & 1)] = sum;
      }
      __syncwarp();
      if (lane == 0) mbar_arrive(B.l_ready);
#pragma unroll
      for (int i = 0; i < 36; i++) l[i] = 0.f;
  };
  PH_DECL;
  for (int r = 0; r < nheads; r++) {
#define SSTAMP(k) do { if (w == SSW && warp_in_wg == 0 && lane == 0 && r < 6) CSTAMP(96 + 4 * r + (k)); } while (0)
    SSTAMP(0);
    {
      auto step = [&](int j, uint32_t& xa, uint32_t& wa, uint32_t& rel_x, uint32_t& rel_w, uint32_t& rel_wr) {
        if (j < 2) {
          mbar_wait(B.xo_full + 8 * j, r & 1);
          xa = sb + A_O + j * BT;
          rel_x = B.xo_empty;
        } else if (j < 4 || j == 6) {
          const int h = j == 3 ? 1 : 0;
          mbar_wait(B.xq_full + 8 * h, h ? (r & 1) : (j == 6 ? 1 : 0));
          xa = sb + A_Q + h * BT;
          rel_x = j == 2 ? B.xq_empty : (j == 6 ? B.xq_done : 0);
        } else {
          const int sl = j == 7 ? 2 : j - 4;
          mbar_wait(B.x_full + 8 * sl, r & 1);
          xa = sb + A_P + sl * BT;
          rel_x = B.b_empty + 8 * sl;
        }
        if (j < 3 || j == 5 || j == 6) {
          const int sl = (kuse + (j < 3 ? j : j - 2)) % 3;
          mbar_wait(B.kw_full + 8 * sl, (kwph >> sl) & 1);
          kwph ^= 1u << sl;
          wa = sb + A_K + sl * 2 * AT + w * AT;
          if (j < 2) { rel_w = B.k_empty + 8 * sl; rel_wr = rk_empty + 8 * sl; }
          else { rel_w = B.k_free + 8 * sl; rel_wr = 0; }
        } else {
          const int sl = (vuse + (j == 7 ? 2 : j - 3)) % 3;
          mbar_wait(B.vw_full + 8 * sl, (vwph >> sl) & 1);
          vwph ^= 1u << sl;
          wa = sb + A_V + sl * 2 * AT + w * AT;
          rel_w = B.v_free + 8 * sl; rel_wr = 0;
        }
      };
      uint32_t xa, wa, rx, rw, rwr, prx, prw, prwr;
      if (r == DBGR && warp_in_wg == 0 && lane == 0) DSTAMP(w * 10 + 8);
      step(0, xa, wa, prx, prw, prwr);
      if (r == DBGR && warp_in_wg == 0 && lane == 0) DSTAMP(w * 10);
      PH(0);
      wg_fence();
      mma_kblock_mn<true>(acc, mkdesc(wa), mkdesc(xa));
      wg_commit();
      if (FLUSH_AT == 0 && r > 1 && w == 1) flush_l();
#pragma unroll
      for (int j = 1; j < 8; j++) {
        step(j, xa, wa, rx, rw, rwr);
        if (r == DBGR && warp_in_wg == 0 && lane == 0) DSTAMP(w * 10 + j);
        PH(0);
        wg_fence();
        mma_kblock_mn<false>(acc, mkdesc(wa), mkdesc(xa));
        wg_commit();
        wg_wait<1>();
        if (lane == 0) { mbar_arrive(prw); if (prwr) mbar_arrive_remote(prwr); if (prx) mbar_arrive(prx); }
        prx = rx; prw = rw; prwr = rwr;
        if (j == FLUSH_AT && r > 1 && w == 1) flush_l();
        PH(1);
      }
      wg_wait<0>();
      if (lane == 0) { mbar_arrive(prw); mbar_arrive(prx); mbar_arrive(B.b_empty);   }
      SSTAMP(1);
      mbar_wait(B.xq_done, r & 1);
      store_tile_scaled(acc, sb + A_Q + w * BT + st_off, qscale);
      fence_async_smem();
      __syncwarp();
      if (lane == 0) mbar_arrive(B.q_ready);
      mbar_wait(B.q_ready, r & 1);
      if (r == 0 && delay > 0) {
        const long long t0 = clock64();
        while (clock64() - t0 < delay) __nanosleep(100);
      }
      SSTAMP(2);
      PH(2);
    }
#pragma unroll 1
    for (int t = w; t < 8; t += 2) {
      const int kslot = (kuse + 5 + t) % 3, slot = (t + 1) % 3;
      mbar_wait(B.k_full + 8 * n6, nph);
      n6 += 2;
      if (n6 >= 6) { n6 -= 6; nph ^= 1; }
      PH(3);
      {
        const desc_t da = mkdesc(sb + A_K + kslot * 2 * AT), db = mkdesc(sb + A_Q);
        wg_fence();
        wgmma144<0, true>(acc, da, db);
#pragma unroll
        for (int kk = 1; kk < 8; kk++)
          wgmma144<0, false>(acc, da + (kk >> 2) * (AT >> 4) + (kk & 3) * 2, db + (kk >> 2) * (BT >> 4) + (kk & 3) * 2);
        wg_commit();
      }
      mbar_wait(B.b_empty + 8 * slot, (((4 + t) / 3) & 1) ^ 1);
      wg_wait<0>();
      if (lane == 0) {
        if (warp_in_wg == 0) *(volatile uint32_t*)(smem + A_BAR + 408 + 4 * w) = 4 * r + (t >> 1) + 1;
        if (t < 5) mbar_arrive2(B.k_free + 8 * kslot);
        else if (r + 1 < nheads) { mbar_arrive2(B.k_empty + 8 * kslot); mbar_arrive2_remote(rk_empty + 8 * kslot); }
        if (t >= 6) mbar_arrive(B.s_done);
      }
      mbar_wait(my_turn, tph);
      tph ^= 1;
      const uint32_t pa = sb + A_P + slot * BT + st_off;
#pragma unroll
      for (int j = 0; j < 18; j += 2) {
        float* e = &acc[4 * j];
#pragma unroll
        for (int i = 0; i < 8; i++) e[i] = ex2(e[i]);
        l[2 * j] += e[0] + e[2];
        l[2 * j + 1] += e[1] + e[3];
        l[2 * j + 2] += e[4] + e[6];
        l[2 * j + 3] += e[5] + e[7];
        stsm_t4(pa + j * 1024, pack_bf16(e[0], e[1]), pack_bf16(e[2], e[3]), pack_bf16(e[4], e[5]), pack_bf16(e[6], e[7]));
        if (j == TURN_AT && lane == 0) mbar_arrive(other_turn);
      }
      fence_async_smem();
      __syncwarp();
      if (lane == 0) mbar_arrive(B.p_full + 8 * slot);
      PH(6);
    }
    kuse = (kuse + 13) % 3;
    vuse = (vuse + 11) % 3;
    SSTAMP(3);
    if (w == 0 || r == 0) flush_l();
  }
  if (w == 1 && nheads > 1) flush_l();
  PH_OUT(88 + 8 * w);
}

__device__ __forceinline__ void att_fallback(uint8_t* img, float* scr, const __nv_bfloat16* xb, const __nv_bfloat16* wq,
                                             const __nv_bfloat16* Kh, const __nv_bfloat16* Vh, int tid) {
  float* ps = scr;
  float* qs = scr + 512;
  float* red = scr + 640;
  const float qscale = 0.08838834764831845f * 1.4426950408889634f;
  for (int q = 0; q < SQ; q++) {
    float qa = 0.f;
    for (int k = 0; k < DM; k++) qa = fmaf(__bfloat162float(xb[q * DM + k]), __bfloat162float(wq[(size_t)k * (NH * DH) + tid]), qa);
    qs[tid] = __bfloat162float(__float2bfloat16(qa * qscale));
    named_bar(1, 128);
    float s[4], m = -INFINITY;
    for (int i = 0; i < 4; i++) {
      const __nv_bfloat16* kr = Kh + (size_t)(tid + 128 * i) * DH;
      float a = 0.f;
      for (int d = 0; d < DH; d++) a = fmaf(qs[d], __bfloat162float(kr[d]), a);
      s[i] = a;
      m = fmaxf(m, a);
    }
    for (int o = 16; o; o >>= 1) m = fmaxf(m, __shfl_xor_sync(0xffffffffu, m, o));
    if ((tid & 31) == 0) red[tid >> 5] = m;
    named_bar(1, 128);
    m = fmaxf(fmaxf(red[0], red[1]), fmaxf(red[2], red[3]));
    float sum = 0.f;
    for (int i = 0; i < 4; i++) {
      const float e = exp2f(s[i] - m);
      sum += e;
      ps[tid + 128 * i] = __bfloat162float(__float2bfloat16(e));
    }
    for (int o = 16; o; o >>= 1) sum += __shfl_xor_sync(0xffffffffu, sum, o);
    if ((tid & 31) == 0) red[4 + (tid >> 5)] = sum;
    named_bar(1, 128);
    sum = red[4] + red[5] + red[6] + red[7];
    float o = 0.f;
    for (int k = 0; k < SK; k++) o = fmaf(ps[k], __bfloat162float(Vh[(size_t)k * DH + tid]), o);
    const int off = (tid >> 6) * BT + q * 128 + (((((tid & 63) >> 3)) ^ (q & 7)) << 4) + (tid & 7) * 2;
    *(__nv_bfloat16*)(img + off) = __float2bfloat16(o / sum);
    named_bar(1, 128);
  }
}

__device__ __forceinline__ void att_o_epilogue(const Params& p, uint32_t sb, uint8_t* smem, const HeadList& hl, int r, int nheads,
                                               int warp_in_wg,
                                               int lane, float (&acc0)[72], float (&acc1)[72]) {
  const AttBars B(sb + A_BAR);
  const int tid = warp_in_wg * 32 + lane;
  const uint32_t st_off = stsm_lane_off(warp_in_wg, lane);
  {
    EP(0);
    mbar_wait(B.l_ready, r & 1);
    float* lp = (float*)(smem + A_L);
    bool bad;
    {
      float l0 = 0.f, l1 = 1.f;
#pragma unroll
      for (int i = 0; i < 8; i++) l0 += lp[i * SQ + tid];
      if (tid < 16) {
        l1 = 0.f;
#pragma unroll
        for (int i = 0; i < 8; i++) l1 += lp[i * SQ + 128 + tid];
      }
      bad = !(l0 >= 5.4e-20f && l0 <= 1.8e19f && l1 >= 5.4e-20f && l1 <= 1.8e19f);
      lp[tid] = __fdividef(1.f, l0);
      if (tid < 16) lp[128 + tid] = __fdividef(1.f, l1);
    }
    named_bar(1, 128);
    EP(1);
    const uint32_t img = sb + A_O + st_off;
    __nv_bfloat162 chk0 = __floats2bfloat162_rn(0.f, 0.f), chk1 = chk0, chk2 = chk0, chk3 = chk0;
    const __nv_bfloat162 zero2 = chk0;
    const float2* li2 = (const float2*)lp + (lane & 3);
    float2 sa = li2[0], sb2 = li2[4], sc = li2[8], sd = li2[12];
    uint32_t a[36], c[36];
#pragma unroll
    for (int j = 0; j < 18; j += 2) {
      const float4 s = make_float4(sa.x, sa.y, sb2.x, sb2.y);
      sa = sc; sb2 = sd;
      if (j + 4 < 18) { sc = li2[4 * (j + 4)]; sd = li2[4 * (j + 5)]; }
      a[2 * j] = pack_bf16(acc0[4 * j] * s.x, acc0[4 * j + 1] * s.y);
      a[2 * j + 1] = pack_bf16(acc0[4 * j + 2] * s.x, acc0[4 * j + 3] * s.y);
      a[2 * j + 2] = pack_bf16(acc0[4 * j + 4] * s.z, acc0[4 * j + 5] * s.w);
      a[2 * j + 3] = pack_bf16(acc0[4 * j + 6] * s.z, acc0[4 * j + 7] * s.w);
      c[2 * j] = pack_bf16(acc1[4 * j] * s.x, acc1[4 * j + 1] * s.y);
      c[2 * j + 1] = pack_bf16(acc1[4 * j + 2] * s.x, acc1[4 * j + 3] * s.y);
      c[2 * j + 2] = pack_bf16(acc1[4 * j + 4] * s.z, acc1[4 * j + 5] * s.w);
      c[2 * j + 3] = pack_bf16(acc1[4 * j + 6] * s.z, acc1[4 * j + 7] * s.w);
      chk0 = __hfma2(*(const __nv_bfloat162*)&a[2 * j], zero2, chk0); chk0 = __hfma2(*(const __nv_bfloat162*)&a[2 * j + 1], zero2, chk0);
      chk1 = __hfma2(*(const __nv_bfloat162*)&a[2 * j + 2], zero2, chk1); chk2 = __hfma2(*(const __nv_bfloat162*)&a[2 * j + 3], zero2, chk2);
      chk3 = __hfma2(*(const __nv_bfloat162*)&c[2 * j], zero2, chk3); chk1 = __hfma2(*(const __nv_bfloat162*)&c[2 * j + 1], zero2, chk1);
      chk2 = __hfma2(*(const __nv_bfloat162*)&c[2 * j + 2], zero2, chk2); chk3 = __hfma2(*(const __nv_bfloat162*)&c[2 * j + 3], zero2, chk3);
    }
    if (r + 1 < nheads) mbar_wait(B.xo_empty, (r + 1) & 1);
    else mbar_wait(B.o_empty, (r & 1) ^ 1);
#pragma unroll
    for (int j = 0; j < 18; j += 2) {
      stsm_t4(img + j * 1024, a[2 * j], a[2 * j + 1], a[2 * j + 2], a[2 * j + 3]);
      stsm_t4(img + BT + j * 1024, c[2 * j], c[2 * j + 1], c[2 * j + 2], c[2 * j + 3]);
    }
    const uint32_t chk = *(const uint32_t*)&chk0 | *(const uint32_t*)&chk1 | *(const uint32_t*)&chk2 | *(const uint32_t*)&chk3;
    bad = bad || ((chk & 0x7fff7fffu) != 0u);
    EP(4);
    uint32_t anybad;
    asm volatile("{\n.reg .pred p, q;\nsetp.ne.u32 p, %1, 0;\nbar.red.or.pred q, 1, 128, p;\nselp.u32 %0, 1, 0, q;\n}\n"
                 : "=r"(anybad)
                 : "r"((uint32_t)bad)
                 : "memory");
    EP(5);
    if (anybad) {
      const HeadId id = att_head(hl, r);
      const int blk = id.g >> 3;
      const size_t hoff = (size_t)((id.g & 7) * NH + id.h) * (SK * DH);
      att_fallback(smem + A_O, (float*)(smem + A_FB), p.X[blk] + (size_t)(id.g & 7) * SQ * DM, p.Wq[blk] + id.h * DH,
                   p.K[blk] + hoff, p.V[blk] + hoff, tid);
    }
    EP(6);
    fence_async_smem();
    __syncwarp();
    if (lane == 0) mbar_arrive(B.o_full);
    EP(7);
  }
}

__device__ __forceinline__ void op_producer(const Params& p, uint32_t sb, uint8_t* smem, int g, int ch, int rank, int warp, int lane) {
  const uint32_t full = sb + O_BAR, empty = full + 8 * O_NS;
  volatile uint32_t* nready = (volatile uint32_t*)(smem + O_BAR + 128);
  if (warp == 1) {
    uint32_t* f = &g_oflag[ch][g * NH + lane];
    bool seen = false;
    uint32_t cnt = 0, n = 0;
    while (cnt < NH) {
      if (!seen) {
        uint32_t v;
        asm volatile("ld.acquire.gpu.global.u32 %0, [%1];" : "=r"(v) : "l"(f) : "memory");
        if (v) {
          seen = true;
          asm volatile("st.relaxed.gpu.global.u32 [%0], %1;" ::"l"(f), "r"(0u) : "memory");
        }
      }
      const uint32_t m = __ballot_sync(0xffffffffu, seen);
      const uint32_t c = m == 0xffffffffu ? 32u : (uint32_t)(__ffs(~m) - 1);
      if (c != cnt) {
        cnt = c;
        __syncwarp();
        if (lane == 0) {
          asm volatile("fence.acq_rel.cta;" ::: "memory");
          *nready = c;
        }
      } else {
        if (++n > (1u << 24)) __trap();
        __nanosleep(40);
      }
    }
    return;
  }
  if (warp != 0 || lane != 0) return;
  const int blk = g >> 3;
  int slot = 0;
  uint32_t ph = 1, have = 0;
  for (int kb = 0; kb < 64; kb++) {
    const int hh = g * NH + (kb >> 1);
    mbar_wait(empty + 8 * slot, ph);
    if (kb >= 40 && kb < 48) DSTAMP(44 + kb - 40);
    mbar_expect_tx(full + 8 * slot, O_STG);
    tma3d_mc(sb + slot * O_STG + rank * 2 * AT, &p.tmWo[blk], 0, kb * 64, ch * 4 + rank * 2, full + 8 * slot);
    if ((uint32_t)(kb >> 1) >= have) {
      uint32_t n = 0;
      while ((have = *nready) <= (uint32_t)(kb >> 1)) {
        if (++n > (1u << 26)) __trap();
      }
      asm volatile("fence.acq_rel.cta;" ::: "memory");
    }
    if ((kb & 1) == 0) TSTAMP(1 + (kb >> 1));
    bulk_load(sb + slot * O_STG + 4 * AT, g_O + (size_t)hh * QIMG + (kb & 1) * BT, BT, full + 8 * slot);
    if (++slot == O_NS) { slot = 0; ph ^= 1; }
  }
}
__device__ __forceinline__ void op_store_tile(const Params& p, uint32_t sb, int g, int ch, int m, const float (&acc)[72], int warp_in_wg,
                                              int lane) {
  store_tile_scaled(acc, sb + m * BT + stsm_lane_off(warp_in_wg, lane), 1.f);
}
__device__ __forceinline__ void op_issue_store(const Params& p, uint32_t sb, int g, int ch, int m) {
  tma2d_store(&p.tmOut, sb + m * BT, (g >> 3) * DM + ch * 256 + m * 64, (g & 7) * SQ);
}
__device__ __forceinline__ void op_consumer1(const Params& p, uint32_t sb, int g, int ch, int rank, int m0, int warp_in_wg,
                                             int lane) {
  const uint32_t full = sb + O_BAR, empty = full + 8 * O_NS, rempty = peer_addr(empty, rank ^ 1);
  float acc0[72];
  int slot = 1, prev = 0;
  uint32_t ph = 0;
  mbar_wait(full, 0);
  wg_fence();
  mma_kblock_mn<true>(acc0, mkdesc(sb + m0 * AT), mkdesc(sb + 4 * AT));
  wg_commit();
  for (int kb = 1; kb < 64; kb++) {
    mbar_wait(full + 8 * slot, ph);
    if (m0 == 0 && warp_in_wg == 0 && lane == 0 && kb >= 40 && kb < 48) DSTAMP(0 + kb - 40);
    wg_fence();
    mma_kblock_mn<false>(acc0, mkdesc(sb + slot * O_STG + m0 * AT), mkdesc(sb + slot * O_STG + 4 * AT));
    wg_commit();
    wg_wait<1>();
    if (lane == 0 && kb - 1 + O_NS < 64) { mbar_arrive(empty + 8 * prev); mbar_arrive_remote(rempty + 8 * prev); }
    prev = slot;
    if (++slot == O_NS) { slot = 0; ph ^= 1; }
  }
  wg_wait<0>();
  named_bar(2, 384);
  op_store_tile(p, sb, g, ch, m0, acc0, warp_in_wg, lane);
  fence_async_smem();
  named_bar(3 + m0, 128);
  if (warp_in_wg == 0 && lane == 0) {
    op_issue_store(p, sb, g, ch, m0);
    bulk_commit();
    bulk_wait_read();
  }
}

__device__ __forceinline__ void wg3_role(const Params& p, uint32_t sb, uint8_t* smem, bool is_att, int g, int idx, int rank,
                                         const HeadList& hl, int nheads, int warp_in_wg, int lane, float (&acc0)[72],
                                         float (&acc1)[72]) {
  if (is_att) {
    const AttBars B(sb + A_BAR);
    const uint32_t rv_empty = peer_addr(B.v_empty, rank ^ 1);
    PH_DECL;
    int slot = 0;
    uint32_t aph = 0;
    uint32_t bph = 0;
    auto sprio = [&](int r, int t) {
      volatile uint32_t* c = (volatile uint32_t*)(smem + A_BAR + 408 + 4 * (t & 1));
      const uint32_t need = 4 * r + ((t + 2) >> 1) + 1;
      uint32_t n = 0;
      while (*c < need && ++n < SPRIO) { }
    };
    for (int r = 0; r < nheads; r++) {
      int bslot = 1;
      {
        mbar_wait(B.v_full + 8 * slot, (aph >> slot) & 1);
        aph ^= 1u << slot;
        mbar_wait(B.p_full + 8 * bslot, (bph >> bslot) & 1);
        bph ^= 1u << bslot;
        sprio(r, 0);
        wg_fence();
        mma_kblock_mn2<true>(acc0, acc1, mkdesc(sb + A_V + slot * 2 * AT), mkdesc(sb + A_P + bslot * BT));
        wg_commit();
        wg_wait<0>();
        if (lane == 0) { mbar_arrive2(B.b_empty + 8 * bslot); mbar_arrive2(B.v_free + 8 * slot); }
        if (++slot == 3) slot = 0;
        if (++bslot == 3) bslot = 0;
      }
      for (int t = 1; t < 8; t++) {
        PH(3);
        mbar_wait(B.v_full + 8 * slot, (aph >> slot) & 1);
        aph ^= 1u << slot;
        PH(0);
        mbar_wait(B.p_full + 8 * bslot, (bph >> bslot) & 1);
        bph ^= 1u << bslot;
        PH(1);
        if (t <= 5) sprio(r, t);
        wg_fence();
        mma_kblock_mn2<false>(acc0, acc1, mkdesc(sb + A_V + slot * 2 * AT), mkdesc(sb + A_P + bslot * BT));
        wg_commit();
        wg_wait<0>();
        if (lane == 0) {
          mbar_arrive2(B.b_empty + 8 * bslot);
          if (t < 5) mbar_arrive2(B.v_free + 8 * slot);
          else if (r + 1 < nheads) { mbar_arrive2(B.v_empty + 8 * slot); mbar_arrive2_remote(rv_empty + 8 * slot); }
        }
        PH(2);
        if (++slot == 3) slot = 0;
        if (++bslot == 3) bslot = 0;
      }
      PH(4);
      if (warp_in_wg == 0 && lane == 0) { CSTAMP(65 + r); TSTAMP(17 + r); }
      att_o_epilogue(p, sb, smem, hl, r, nheads, warp_in_wg, lane, acc0, acc1);
      if (warp_in_wg == 0 && lane == 0) CSTAMP(73 + r);
      PH(5);
    }
    PH_OUT(104);
  } else {
    const uint32_t full = sb + O_BAR, empty = full + 8 * O_NS, rempty = peer_addr(empty, rank ^ 1);
    int slot = 1, prev = 0;
    uint32_t ph = 0;
    mbar_wait(full, 0);
    wg_fence();
    mma_kblock_mn<true>(acc0, mkdesc(sb + 2 * AT), mkdesc(sb + 4 * AT));
    wg_commit();
    mma_kblock_mn<true>(acc1, mkdesc(sb + 3 * AT), mkdesc(sb + 4 * AT));
    wg_commit();
    for (int kb = 1; kb < 64; kb++) {
      mbar_wait(full + 8 * slot, ph);
      if (warp_in_wg == 0 && lane == 0 && kb >= 40 && kb < 48) DSTAMP(10 + kb - 40);
      const desc_t da = mkdesc(sb + slot * O_STG + 2 * AT), db = mkdesc(sb + slot * O_STG + 4 * AT);
      wg_fence();
      mma_kblock_mn<false>(acc0, da, db);
      wg_commit();
      wg_wait<1>();
      if (lane == 0 && kb - 1 + O_NS < 64) { mbar_arrive(empty + 8 * prev); mbar_arrive_remote(rempty + 8 * prev); }
      wg_fence();
      mma_kblock_mn<false>(acc1, da + (AT >> 4), db);
      wg_commit();
      prev = slot;
      if (++slot == O_NS) { slot = 0; ph ^= 1; }
    }
    wg_wait<0>();
    named_bar(2, 384);
    op_store_tile(p, sb, g, idx, 2, acc0, warp_in_wg, lane);
    op_store_tile(p, sb, g, idx, 3, acc1, warp_in_wg, lane);
    fence_async_smem();
    named_bar(5, 128);
    if (warp_in_wg == 0 && lane == 0) {
      op_issue_store(p, sb, g, idx, 2);
      op_issue_store(p, sb, g, idx, 3);
      bulk_commit();
      bulk_wait_read();
      TSTAMP(40);
    }
  }
}

__global__ void __launch_bounds__(NTHREADS, 1) fused_attn_kernel(const __grid_constant__ Params p) {
  extern __shared__ __align__(1024) uint8_t smem[];
  const uint32_t sb = smem_u32(smem);
  const int warp = __shfl_sync(0xffffffffu, threadIdx.x >> 5, 0), lane = threadIdx.x & 31;
  const int wg = warp >> 2, warp_in_wg = warp & 3;
  const int rank = blockIdx.x & 1;
  const int npair = gridDim.x >> 1, ps = npair >> 1;
  volatile int* s_slot = (volatile int*)(smem + SMEM_BYTES - 16);
  if (threadIdx.x == 0 && rank == 0) {
    int slot = blockIdx.x >> 1;
    if (p.sidemap) {
      uint32_t v, t0, t1, best = 0xffffffffu;
      for (int i = 0; i < 2; i++) {
        asm volatile("mov.u32 %0, %clock;" : "=r"(t0)::"memory");
        asm volatile("atom.global.add.u32 %0, [%1], 0;" : "=r"(v) : "l"(&g_probe[0]) : "memory");
        asm volatile("{\n.reg .pred p;\nsetp.ne.u32 p, %1, 0x7fffffff;\nmov.u32 %0, 0;\n@p mov.u32 %0, %clock;\n}\n" : "=r"(t1) : "r"(v) : "memory");
        best = min(best, t1 - t0);
      }
      const int side = best > SIDE_THR ? 1 : 0;
      const int t = (int)atomicAdd(&g_ticket[side][0], 1);
      slot = t < ps ? side * ps + t : (side ^ 1) * ps + ps - 1 - (t - ps);
    }
    s_slot[0] = slot;
  }
  if (threadIdx.x == 32) {
    const AttBars B(sb + A_BAR);
    for (int i = 0; i < 6; i++) mbar_init(B.k_full + 8 * i, 1);
    for (int i = 0; i < 3; i++) {
      mbar_init(B.kw_full + 8 * i, 1); mbar_init(B.k_empty + 8 * i, 16); mbar_init(B.k_free + 8 * i, 8); mbar_init(B.v_free + 8 * i, 8);
      mbar_init(B.vw_full + 8 * i, 1); mbar_init(B.v_full + 8 * i, 1); mbar_init(B.v_empty + 8 * i, 16);
      mbar_init(B.x_full + 8 * i, 1); mbar_init(B.p_full + 8 * i, 4); mbar_init(B.b_empty + 8 * i, 8);
    }
    for (int i = 0; i < 2; i++) { mbar_init(B.xq_full + 8 * i, 1); mbar_init(B.xo_full + 8 * i, 1); }
    mbar_init(B.s_done, 8); mbar_init(B.xo_empty, 16); mbar_init(B.xq_empty, 8); mbar_init(B.xq_done, 8);
    mbar_init(B.q_ready, 8); mbar_init(B.l_ready, 8);
    mbar_init(B.o_full, 4); mbar_init(B.o_empty, 1);
    for (int i = 0; i < 8; i++) mbar_init(B.turn + 8 * i, 1);
    mbar_init(sb + A_BAR + 400, 1);
    *(volatile uint32_t*)(smem + A_BAR + 408) = 0;
    *(volatile uint32_t*)(smem + A_BAR + 412) = 0;
    asm volatile("fence.mbarrier_init.release.cluster;" ::: "memory");
  }
  if (threadIdx.x == 64) {
    for (int i = 0; i < 2; i++) {
      asm volatile("prefetch.tensormap [%0];" ::"l"(&p.tmK[i]) : "memory");
      asm volatile("prefetch.tensormap [%0];" ::"l"(&p.tmV[i]) : "memory");
      asm volatile("prefetch.tensormap [%0];" ::"l"(&p.tmWq[i]) : "memory");
      asm volatile("prefetch.tensormap [%0];" ::"l"(&p.tmX[i]) : "memory");
      asm volatile("prefetch.tensormap [%0];" ::"l"(&p.tmWo[i]) : "memory");
    }
  }
  asm volatile("barrier.cluster.arrive.release.aligned;\nbarrier.cluster.wait.acquire.aligned;" ::: "memory");
  int pslot;
  asm volatile("ld.shared::cluster.s32 %0, [%1];" : "=r"(pslot) : "r"(peer_addr(sb + SMEM_BYTES - 16, 0)) : "memory");
  pslot = __shfl_sync(0xffffffffu, pslot, 0);
  if (p.sidemap && threadIdx.x == 32 && rank == 0) {
    if (atomicAdd(&g_done, 1) == (uint32_t)npair - 1) { g_ticket[0][0] = 0; g_ticket[1][0] = 0; g_done = 0; __threadfence(); }
  }
  const int blk = pslot >= ps ? 1 : 0, pr = pslot - blk * ps;
  const bool is_op = (pr & 3) == 3 && pr < 32;
  int g = 0, idx = 0, nheads;
  HeadList hl;
  hl.blk = blk;
  hl.stride = p.natt;
  hl.full = p.natt + 16;
  if (is_op) {
    const int m = pr >> 2;
    g = blk * 8 + 2 * (m >> 1) + rank;
    idx = m & 1;
    hl.i0 = NEARLY + 2 * m + rank;
    hl.i2 = 0;
    nheads = OPH;
  } else {
    const int i = 2 * (pr - min((pr + 1) >> 2, 8)) + rank;
    idx = i;
    hl.i0 = i < NEARLY ? i : i + 16;
    hl.i2 = OPH * hl.full + i;
    nheads = OPH + (8 * NH - hl.i2 + p.natt - 1) / p.natt;
  }
  if (threadIdx.x == 0) { TSTAMP(0); CSTAMP(64); }

  auto switch_role = [&](bool init) {
    named_bar(6, NTHREADS);
    if (init) {
      for (int i = 0; i < O_NS; i++) { mbar_init(sb + O_BAR + 8 * i, 1); mbar_init(sb + O_BAR + 8 * O_NS + 8 * i, 24); }
      *(volatile uint32_t*)(smem + O_BAR + 128) = 0;
      asm volatile("fence.mbarrier_init.release.cluster;" ::: "memory");
      const uint32_t sw = sb + A_BAR + 400;
      asm volatile("mbarrier.arrive.release.cluster.shared::cluster.b64 _, [%0];" ::"r"(peer_addr(sw, rank ^ 1)) : "memory");
      uint32_t ok, n = 0;
      do {
        asm volatile("{\n.reg .pred p;\nmbarrier.try_wait.parity.acquire.cluster.shared::cta.b64 p, [%1], 0;\nselp.u32 %0, 1, 0, p;\n}\n"
                     : "=r"(ok) : "r"(sw) : "memory");
        if (++n > WAIT_LIMIT) __trap();
      } while (!ok);
    }
    named_bar(7, NTHREADS);
  };
  const bool run_att = p.mode != 3, run_op = is_op && p.mode != 2;

  if (wg == 0) {
    asm volatile("setmaxnreg.dec.sync.aligned.u32 32;");
    if (run_att) att_producer(p, sb, hl, rank, nheads, warp, lane);
    if (run_op) {
      __syncwarp();
      switch_role(threadIdx.x == 0);
      op_producer(p, sb, smem, g, idx, rank, warp, lane);
    }
  } else if (wg == 3) {
    asm volatile("setmaxnreg.inc.sync.aligned.u32 176;");
    float acc0[72], acc1[72];
    const int ph0 = run_att ? 0 : 1, ph1 = run_op ? 2 : 1;
#pragma unroll 1
    for (int phase = ph0; phase < ph1; phase++) {
      if (phase == 1) switch_role(false);
      wg3_role(p, sb, smem, phase == 0, g, idx, rank, hl, nheads, warp_in_wg, lane, acc0, acc1);
    }
  } else {
    asm volatile("setmaxnreg.inc.sync.aligned.u32 152;");
    if (run_att) {
      att_s_role(sb, smem, wg - 1, rank, nheads, is_op ? 0 : (int)(STAG_EXPR), warp_in_wg, lane);
    }
    if (run_op) {
      switch_role(false);
      op_consumer1(p, sb, g, idx, rank, wg - 1, warp_in_wg, lane);
    }
  }
}

typedef CUresult (*EncodeFn)(CUtensorMap*, CUtensorMapDataType, cuuint32_t, void*, const cuuint64_t*, const cuuint64_t*,
                             const cuuint32_t*, const cuuint32_t*, CUtensorMapInterleave, CUtensorMapSwizzle,
                             CUtensorMapL2promotion, CUtensorMapFloatOOBfill);

void make_map(EncodeFn enc, CUtensorMap* m, const void* ptr, int rank, const cuuint64_t* dims, const cuuint64_t* strides,
              const cuuint32_t* box) {
  const cuuint32_t es[3] = {1, 1, 1};
  CUresult r = enc(m, CU_TENSOR_MAP_DATA_TYPE_BFLOAT16, rank, const_cast<void*>(ptr), dims, strides, box, es,
                   CU_TENSOR_MAP_INTERLEAVE_NONE, CU_TENSOR_MAP_SWIZZLE_128B, L2PROMO,
                   CU_TENSOR_MAP_FLOAT_OOB_FILL_NONE);
  (void)r;
}

}

#define KERNEL_MODE_SEQ 0

extern "C" void kernel_launch(void* const* d_in, const int* in_sizes, int n_in, void* d_out, int out_size) {
  (void)in_sizes; (void)n_in; (void)out_size;
  void* fn = nullptr;
  cudaDriverEntryPointQueryResult qr;
  cudaGetDriverEntryPoint("cuTensorMapEncodeTiled", &fn, cudaEnableDefault, &qr);
  EncodeFn enc = (EncodeFn)fn;
  Params p;
  for (int blk = 0; blk < 2; blk++) {
    const void* x = d_in[blk * 5 + 0];
    const void* k = d_in[blk * 5 + 1];
    const void* v = d_in[blk * 5 + 2];
    const void* wq = d_in[blk * 5 + 3];
    const void* wo = d_in[blk * 5 + 4];
    {
      const cuuint64_t dims[3] = {64, (cuuint64_t)NBATCH * NH * SK, 2}, str[2] = {256, 128};
      const cuuint32_t box[3] = {64, 64, 2};
      make_map(enc, &p.tmK[blk], k, 3, dims, str, box);
      make_map(enc, &p.tmV[blk], v, 3, dims, str, box);
    }
    {
      const cuuint64_t dims[3] = {64, DM, (cuuint64_t)NH * 2}, str[2] = {NH * DH * 2, 128};
      const cuuint32_t box[3] = {64, 64, 1};
      make_map(enc, &p.tmWq[blk], wq, 3, dims, str, box);
    }
    {
      const cuuint64_t dims[3] = {64, (cuuint64_t)NH * DH, 8}, str[2] = {DM * 2, 128};
      const cuuint32_t box[3] = {64, 64, 2};
      make_map(enc, &p.tmWo[blk], wo, 3, dims, str, box);
    }
    {
      const cuuint64_t dims[2] = {DM, (cuuint64_t)NBATCH * SQ}, str[1] = {DM * 2};
      const cuuint32_t box[2] = {64, SQ};
      make_map(enc, &p.tmX[blk], x, 2, dims, str, box);
    }
    p.K[blk] = (const __nv_bfloat16*)k;
    p.V[blk] = (const __nv_bfloat16*)v;
    p.X[blk] = (const __nv_bfloat16*)x;
    p.Wq[blk] = (const __nv_bfloat16*)wq;
    p.Wo[blk] = (const __nv_bfloat16*)wo;
  }
  {
    const cuuint64_t dims[2] = {2 * DM, (cuuint64_t)NBATCH * SQ}, str[1] = {2 * DM * 2};
    const cuuint32_t box[2] = {64, SQ};
    make_map(enc, &p.tmOut, d_out, 2, dims, str, box);
  }
  cudaFuncSetAttribute(fused_attn_kernel, cudaFuncAttributeMaxDynamicSharedMemorySize, SMEM_BYTES);
  int nsm = 132;
  cudaDeviceGetAttribute(&nsm, cudaDevAttrMultiProcessorCount, 0);
  if (nsm > 132) nsm = 132;
  nsm &= ~3;
  p.natt = nsm / 2 - 16;
  p.sidemap = 1;
  cudaLaunchConfig_t cfg = {};
  cfg.gridDim = dim3(nsm);
  cfg.blockDim = dim3(NTHREADS);
  cfg.dynamicSmemBytes = SMEM_BYTES;
  cfg.stream = cudaStreamPerThread;
  cudaLaunchAttribute at[1];
  at[0].id = cudaLaunchAttributeClusterDimension;
  at[0].val.clusterDim.x = 2;
  at[0].val.clusterDim.y = 1;
  at[0].val.clusterDim.z = 1;
  cfg.attrs = at;
  cfg.numAttrs = 1;
  p.mode = 0;
  cudaLaunchKernelEx(&cfg, fused_attn_kernel, p);
}
```
